```python
import torch

def _softmax(x, axis=-1):
    return torch.softmax(x, dim=axis)
def _gelu(x):
    return torch.nn.functional.gelu(x, approximate="tanh")
def _silu(x):
    return torch.nn.functional.silu(x)
def _sigmoid(x):
    return torch.sigmoid(x)
def _layernorm(x, axis=-1, eps=1e-5):
    m = x.mean(dim=axis, keepdim=True)
    v = x.var(dim=axis, keepdim=True, unbiased=False)
    return (x - m) / torch.sqrt(v + eps)
def _scatter_add(tgt, idx, src, axis=0):
    return tgt.clone().index_add_(axis, idx, src)
def _segment_sum(src, seg, n):
    out = torch.zeros((n,) + src.shape[1:], dtype=src.dtype)
    return out.index_add_(0, seg, src)
def _pad(x, pw):
    flat = tuple(v for pair in reversed(pw) for v in pair)
    return torch.nn.functional.pad(x, flat)

kernel_name = 'concat_heads__gqa_block_cached__gqa_block_cached__decode'

def setup_inputs():

    _w = (lambda a: (lambda t: t.to(torch.bfloat16) if t.is_floating_point() else t)(torch.as_tensor(a)))
    def _A_setup():
        B, Sq, D = 1, 1, 448
        Hq, Hkv, Sk, Dh = 16, 8, 65536, 256
        assert Hq % Hkv == 0, (Hq, Hkv)
        return {
            "x": _w((lambda *s: torch.randn(*s, dtype=torch.bfloat16) * 0.8)(B, Sq, D)),
            "k_cache": _w((lambda *s: torch.randn(*s, dtype=torch.bfloat16) * 0.8)(B, Hkv, Sk, Dh)),
            "v_cache": _w((lambda *s: torch.randn(*s, dtype=torch.bfloat16) * 0.05)(B, Hkv, Sk, Dh)),
            "wq": _w((lambda *s: torch.randn(*s, dtype=torch.bfloat16) * 0.8)(D, Hq * Dh) * (D ** -0.5)),
            "wo": _w((lambda *s: torch.randn(*s, dtype=torch.bfloat16) * 0.05)(Hq * Dh, D) * ((Hq * Dh) ** -0.5)),
        }
    _A_in = _A_setup()

    def _B_setup():
        B, Sq, D = 1, 1, 448
        Hq, Hkv, Sk, Dh = 16, 8, 65536, 256
        assert Hq % Hkv == 0, (Hq, Hkv)
        return {
            "x": _w((lambda *s: torch.randn(*s, dtype=torch.bfloat16) * 0.8)(B, Sq, D)),
            "k_cache": _w((lambda *s: torch.randn(*s, dtype=torch.bfloat16) * 0.8)(B, Hkv, Sk, Dh)),
            "v_cache": _w((lambda *s: torch.randn(*s, dtype=torch.bfloat16) * 0.05)(B, Hkv, Sk, Dh)),
            "wq": _w((lambda *s: torch.randn(*s, dtype=torch.bfloat16) * 0.8)(D, Hq * Dh) * (D ** -0.5)),
            "wo": _w((lambda *s: torch.randn(*s, dtype=torch.bfloat16) * 0.05)(Hq * Dh, D) * ((Hq * Dh) ** -0.5)),
        }
    _B_in = _B_setup()

    return {
        "A_x": _A_in["x"],
        "A_k_cache": _A_in["k_cache"],
        "A_v_cache": _A_in["v_cache"],
        "A_wq": _A_in["wq"],
        "A_wo": _A_in["wo"],
        "B_x": _B_in["x"],
        "B_k_cache": _B_in["k_cache"],
        "B_v_cache": _B_in["v_cache"],
        "B_wq": _B_in["wq"],
        "B_wo": _B_in["wo"],
    }

def reference(A_x, A_k_cache, A_v_cache, A_wq, A_wo, B_x, B_k_cache, B_v_cache, B_wq, B_wo):
    def _A_ref(x, k_cache, v_cache, wq, wo):
        B, Sq, D = x.shape
        Hq, Dh = 16, 256
        Hkv = k_cache.shape[1]
        rep = Hq // Hkv
        q = (lambda x, *d: x.permute(*d))((x @ wq).reshape(B, Sq, Hq, Dh), 0, 2, 1, 3)
        k = (lambda x, n, axis: torch.repeat_interleave(x, n, dim=axis))(k_cache, rep, axis=1)
        v = (lambda x, n, axis: torch.repeat_interleave(x, n, dim=axis))(v_cache, rep, axis=1)
        scores = torch.einsum("bhqd,bhkd->bhqk", q, k) * (Dh ** -0.5)
        p = _softmax(scores, axis=-1)
        o = torch.einsum("bhqk,bhkd->bhqd", p, v)
        return (lambda x, *d: x.permute(*d))(o, 0, 2, 1, 3).reshape(B, Sq, Hq * Dh) @ wo

    def _B_ref(x, k_cache, v_cache, wq, wo):
        B, Sq, D = x.shape
        Hq, Dh = 16, 256
        Hkv = k_cache.shape[1]
        rep = Hq // Hkv
        q = (lambda x, *d: x.permute(*d))((x @ wq).reshape(B, Sq, Hq, Dh), 0, 2, 1, 3)
        k = (lambda x, n, axis: torch.repeat_interleave(x, n, dim=axis))(k_cache, rep, axis=1)
        v = (lambda x, n, axis: torch.repeat_interleave(x, n, dim=axis))(v_cache, rep, axis=1)
        scores = torch.einsum("bhqd,bhkd->bhqk", q, k) * (Dh ** -0.5)
        p = _softmax(scores, axis=-1)
        o = torch.einsum("bhqk,bhkd->bhqd", p, v)
        return (lambda x, *d: x.permute(*d))(o, 0, 2, 1, 3).reshape(B, Sq, Hq * Dh) @ wo

    a = _A_ref(A_x, A_k_cache, A_v_cache, A_wq, A_wo)
    b = _B_ref(B_x, B_k_cache, B_v_cache, B_wq, B_wo)
    return torch.concatenate([a, b], axis=-1)
```

```cpp
#include <cuda_runtime.h>
#include <cuda_bf16.h>
#include <stdint.h>

#define NSLOT 6
#define INFLIGHT 3
#define ENDGAME 3
#define ENDFETCH 2
#define WO_INFLIGHT 3
#define RETIRE 4
#define QDELAY 4000
#define WARMUP 1

namespace {

constexpr int kD        = 448;
constexpr int kHD       = 4096;
constexpr int kSegs     = 16;
constexpr int kTilesSeg = 2048;
constexpr int kTiles    = kSegs * kTilesSeg;
constexpr int kMaxCtas  = 144;
constexpr int kSvcCtas  = 128;

constexpr int kThreads    = 352;
constexpr int kSvcThreads = 256;

constexpr uint32_t kUnit     = 16384;
constexpr uint32_t kSlot     = 2 * kUnit;
constexpr uint32_t kWoBytes  = 64 * kD * 2;
constexpr uint32_t kOffQ     = NSLOT * kSlot;
constexpr uint32_t kOffStage = kOffQ + 16384;
constexpr uint32_t kOffRed   = kOffStage + 4096;
constexpr uint32_t kOffML    = kOffRed + 8 * 72 * 4;
constexpr uint32_t kOffMisc  = kOffML + 128;
constexpr uint32_t kSmemBytes = kOffMisc + 512;

constexpr float kScaleLog2 = 0.0625f * 1.4426950408889634f;
constexpr float kNegBig    = -3.0e38f;

struct Params {
    const __nv_bfloat16* x[2];
    const char* k[2];
    const char* v[2];
    const __nv_bfloat16* wq[2];
    const __nv_bfloat16* wo[2];
    __nv_bfloat16* out;
};

constexpr int kSets = 4;
constexpr int kRec  = 544;
__device__ unsigned int g_tile_ctr;
__device__ __align__(128) uint32_t g_q[2 * kHD];
__device__ __align__(128) uint32_t g_part[kSets * kMaxCtas * kRec];
__device__ __align__(128) uint32_t g_cdone[kSvcCtas];
__device__ __align__(128) uint32_t g_out_part[kSvcCtas * kD];
#define TL(i) do { } while (0)
#define TLMAX(i) do { } while (0)

constexpr uint32_t kSpinLimit = 1u << 22;
__device__ __forceinline__ uint32_t smem_u32(const void* p) { return (uint32_t)__cvta_generic_to_shared(p); }
__device__ __forceinline__ void mbar_init(uint32_t bar, uint32_t cnt) {
    asm volatile("mbarrier.init.shared::cta.b64 [%0], %1;" :: "r"(bar), "r"(cnt) : "memory");
}
__device__ __forceinline__ void mbar_expect_tx(uint32_t bar, uint32_t bytes) {
    asm volatile("mbarrier.arrive.expect_tx.shared::cta.b64 _, [%0], %1;" :: "r"(bar), "r"(bytes) : "memory");
}
__device__ __forceinline__ void mbar_arrive(uint32_t bar) {
    asm volatile("mbarrier.arrive.shared::cta.b64 _, [%0];" :: "r"(bar) : "memory");
}
__device__ __forceinline__ void mbar_wait(uint32_t bar, uint32_t parity) {
    uint32_t ok;
    uint32_t spins = 0;
    while (true) {
        asm volatile("{\n.reg .pred p;\nmbarrier.try_wait.parity.shared::cta.b64 p, [%1], %2;\nselp.u32 %0, 1, 0, p;\n}"
                     : "=r"(ok) : "r"(bar), "r"(parity) : "memory");
        if (ok) break;
        if (++spins > kSpinLimit) __trap();
    }
}
__device__ __forceinline__ void bulk_g2s(uint32_t dst, const void* src, uint32_t bytes, uint32_t bar, uint64_t pol) {
    asm volatile("cp.async.bulk.shared::cluster.global.mbarrier::complete_tx::bytes.L2::cache_hint [%0], [%1], %2, [%3], %4;"
                 :: "r"(dst), "l"(src), "r"(bytes), "r"(bar), "l"(pol) : "memory");
}
__device__ __forceinline__ uint32_t ld_relaxed1(const void* p) {
    uint32_t v;
    asm volatile("ld.relaxed.gpu.global.u32 %0, [%1];" : "=r"(v) : "l"(p) : "memory");
    return v;
}
__device__ __forceinline__ void st_relaxed4(void* p, uint4 v) {
    asm volatile("st.relaxed.gpu.global.v4.u32 [%0], {%1,%2,%3,%4};" :: "l"(p), "r"(v.x), "r"(v.y), "r"(v.z), "r"(v.w) : "memory");
}
__device__ __forceinline__ void st_relaxed2(void* p, uint2 v) {
    asm volatile("st.relaxed.gpu.global.v2.u32 [%0], {%1,%2};" :: "l"(p), "r"(v.x), "r"(v.y) : "memory");
}
__device__ __forceinline__ void st_relaxed1(void* p, uint32_t v) {
    asm volatile("st.relaxed.gpu.global.u32 [%0], %1;" :: "l"(p), "r"(v) : "memory");
}
__device__ __forceinline__ uint32_t tagf(float v, uint32_t tag) { return (__float_as_uint(v) & ~1u) | tag; }
__device__ __forceinline__ void repoll4(uint4& v, const void* p, uint32_t tag, uint32_t& bad) {
    asm volatile("{\n.reg .pred p;\n.reg .b32 a, b;\n"
                 "lop3.b32 a, %0, %1, %5, 0x7E;\nlop3.b32 b, %2, %3, %5, 0x7E;\nlop3.b32 a, a, b, 1, 0xA8;\n"
                 "setp.ne.u32 p, a, 0;\n"
                 "@p ld.relaxed.gpu.global.v4.u32 {%0,%1,%2,%3}, [%6];\n"
                 "or.b32 %4, %4, a;\n}"
                 : "+r"(v.x), "+r"(v.y), "+r"(v.z), "+r"(v.w), "+r"(bad) : "r"(tag), "l"(p) : "memory");
}
__device__ __forceinline__ void repoll2(uint2& v, const void* p, uint32_t tag, uint32_t& bad) {
    asm volatile("{\n.reg .pred p;\n.reg .b32 a;\n"
                 "lop3.b32 a, %0, %1, %3, 0x7E;\nand.b32 a, a, 1;\n"
                 "setp.ne.u32 p, a, 0;\n"
                 "@p ld.relaxed.gpu.global.v2.u32 {%0,%1}, [%4];\n"
                 "or.b32 %2, %2, a;\n}"
                 : "+r"(v.x), "+r"(v.y), "+r"(bad) : "r"(tag), "l"(p) : "memory");
}
__device__ __forceinline__ void bar_sync(int id, int n) { asm volatile("bar.sync %0, %1;" :: "r"(id), "r"(n) : "memory"); }
__device__ __forceinline__ uint4 lds128(uint32_t a) {
    uint4 v;
    asm volatile("ld.shared.v4.u32 {%0,%1,%2,%3}, [%4];" : "=r"(v.x), "=r"(v.y), "=r"(v.z), "=r"(v.w) : "r"(a) : "memory");
    return v;
}
__device__ __forceinline__ float4 lds128f(uint32_t a) {
    float4 v;
    asm volatile("ld.shared.v4.f32 {%0,%1,%2,%3}, [%4];" : "=f"(v.x), "=f"(v.y), "=f"(v.z), "=f"(v.w) : "r"(a) : "memory");
    return v;
}
__device__ __forceinline__ float2 lds64f(uint32_t a) {
    float2 v;
    asm volatile("ld.shared.v2.f32 {%0,%1}, [%2];" : "=f"(v.x), "=f"(v.y) : "r"(a) : "memory");
    return v;
}
__device__ __forceinline__ uint32_t lds32(uint32_t a) {
    uint32_t v;
    asm volatile("ld.shared.u32 %0, [%1];" : "=r"(v) : "r"(a) : "memory");
    return v;
}
__device__ __forceinline__ void sts128f(uint32_t a, float4 v) {
    asm volatile("st.shared.v4.f32 [%0], {%1,%2,%3,%4};" :: "r"(a), "f"(v.x), "f"(v.y), "f"(v.z), "f"(v.w) : "memory");
}
__device__ __forceinline__ void sts64(uint32_t a, uint32_t x, uint32_t y) {
    asm volatile("st.shared.v2.u32 [%0], {%1,%2};" :: "r"(a), "r"(x), "r"(y) : "memory");
}
__device__ __forceinline__ void sts32(uint32_t a, uint32_t v) {
    asm volatile("st.shared.u32 [%0], %1;" :: "r"(a), "r"(v) : "memory");
}
__device__ __forceinline__ void sts32f(uint32_t a, float v) { sts32(a, __float_as_uint(v)); }
__device__ __forceinline__ void ldsm4t(uint32_t a, uint32_t& r0, uint32_t& r1, uint32_t& r2, uint32_t& r3) {
    asm volatile("ldmatrix.sync.aligned.m8n8.x4.trans.shared.b16 {%0,%1,%2,%3}, [%4];"
                 : "=r"(r0), "=r"(r1), "=r"(r2), "=r"(r3) : "r"(a) : "memory");
}
__device__ __forceinline__ void mma16816(float (&d)[4], uint32_t a0, uint32_t a1, uint32_t a2, uint32_t a3, uint32_t b0, uint32_t b1) {
    asm volatile("mma.sync.aligned.m16n8k16.row.col.f32.bf16.bf16.f32 {%0,%1,%2,%3}, {%4,%5,%6,%7}, {%8,%9}, {%0,%1,%2,%3};"
                 : "+f"(d[0]), "+f"(d[1]), "+f"(d[2]), "+f"(d[3])
                 : "r"(a0), "r"(a1), "r"(a2), "r"(a3), "r"(b0), "r"(b1));
}
__device__ __forceinline__ float ex2(float x) { float y; asm("ex2.approx.ftz.f32 %0, %1;" : "=f"(y) : "f"(x)); return y; }
__device__ __forceinline__ float rcp(float x) { float y; asm("rcp.approx.ftz.f32 %0, %1;" : "=f"(y) : "f"(x)); return y; }
__device__ __forceinline__ uint32_t pack_bf16(float lo, float hi) {
    uint32_t r; asm("cvt.rn.bf16x2.f32 %0, %1, %2;" : "=r"(r) : "f"(hi), "f"(lo)); return r;
}
__device__ __forceinline__ float bf_lo(uint32_t u) { return __uint_as_float(u << 16); }
__device__ __forceinline__ float bf_hi(uint32_t u) { return __uint_as_float(u & 0xffff0000u); }
__device__ __forceinline__ float asf(uint32_t u) { return __uint_as_float(u); }
__device__ __forceinline__ float warp_max(float v) {
    int i = __float_as_int(v);
    i ^= (i >> 31) & 0x7fffffff;
    i = __reduce_max_sync(0xffffffffu, i);
    i ^= (i >> 31) & 0x7fffffff;
    return __int_as_float(i);
}
__device__ __forceinline__ uint32_t seg_tag(int seg) { return ((seg / kSets) & 1) ^ 1; }

__global__ void __launch_bounds__(kThreads, 1) gqa_decode_kernel(const __grid_constant__ Params P) {
    extern __shared__ __align__(128) unsigned char smem[];
    const uint32_t sb = smem_u32(smem);
    const uint32_t bar_full  = sb + kOffMisc;
    const uint32_t bar_empty = bar_full + 16 * NSLOT;
    const uint32_t bar_wo    = bar_empty + 8 * NSLOT;
    const uint32_t bar_svc   = bar_wo + 32;
    const uint32_t bar_q     = bar_svc + 8;
    const uint32_t bar_tag   = bar_q + 16;
    const uint32_t s_tile    = sb + kOffMisc + 256;
    const uint32_t s_ml      = sb + kOffMisc + 320;
    const uint32_t s_tag     = sb + kOffMisc + 384;
    const uint32_t s_wo      = sb + kOffMisc + 392;
    const uint32_t s_owed    = sb + kOffMisc + 400;

    const int tid = threadIdx.x, warp = tid >> 5, lane = tid & 31;
    const int cta = blockIdx.x, ncta = gridDim.x;

    uint64_t pol = 0;
    if (tid == 0) {
        TL(0);
        asm volatile("createpolicy.fractional.L2::evict_first.b64 %0, 1.0;" : "=l"(pol));
        mbar_init(bar_full, 1);
        mbar_init(bar_full + 8, 1);
        mbar_init(bar_full + 16, 1);
        asm volatile("fence.proxy.async.shared::cta;" ::: "memory");
        mbar_expect_tx(bar_full, kUnit);
        bulk_g2s(sb, P.k[0] + (size_t)cta * kUnit, kUnit, bar_full, pol);
        mbar_expect_tx(bar_full + 8, kUnit);
        bulk_g2s(sb + kUnit, P.v[0] + (size_t)cta * kUnit, kUnit, bar_full + 8, pol);
        mbar_expect_tx(bar_full + 16, kUnit);
        bulk_g2s(sb + kSlot, P.k[0] + (size_t)(ncta + cta) * kUnit, kUnit, bar_full + 16, pol);
        TL(16);
        sts64(s_tile, cta, ncta + cta);
        sts64(s_wo, sb, sb);
        for (int s = 3; s < 2 * NSLOT; s++) mbar_init(bar_full + 8 * s, 1);
        for (int s = 0; s < NSLOT; s++) mbar_init(bar_empty + 8 * s, 2);
        for (int s = 0; s < 4; s++) mbar_init(bar_wo + 8 * s, 1);
        mbar_init(bar_svc, 1);
        mbar_init(bar_q, 4);
        mbar_init(bar_q + 8, 8);
        mbar_init(bar_tag, 1);
        asm volatile("fence.proxy.async.shared::cta;" ::: "memory");
    }
    __syncthreads();

    if (warp == 0) {
        if (lane == 0) {
            const char* k0 = P.k[0]; const char* k1 = P.k[1];
            const char* v0 = P.v[0]; const char* v1 = P.v[1];
            int wunit = 0; uint32_t wph = 0;
            int units = 3;
            auto fetch = [&]() {
                uint32_t r;
                asm volatile("atom.relaxed.gpu.global.inc.u32 %0, [%1], 0xffffffff;" : "=r"(r) : "l"(&g_tile_ctr) : "memory");
                return r;
            };
            auto throttle = [&](int limit) {
                while (units >= limit) {
                    mbar_wait(bar_full + 8 * wunit, wph);
                    if (++wunit == 2 * NSLOT) { wunit = 0; wph ^= 1; }
                    units--;
                }
            };
            uint32_t raw = fetch();
            throttle(INFLIGHT);
            mbar_expect_tx(bar_full + 24, kUnit);
            bulk_g2s(sb + kSlot + kUnit, v0 + (size_t)(ncta + cta) * kUnit, kUnit, bar_full + 24, pol);
            units++;
            sts32(s_tag, ((raw >> 15) & 1u) ^ 1u);
            mbar_arrive(bar_tag);
            int slot = 2; uint32_t eph = 1;
            uint32_t cur = 2 * ncta + (raw & (kTiles - 1));
            const uint32_t retire  = ((cta >> 3) == kSegs - 1) ? kTiles - RETIRE * ncta : kTiles;
            const uint32_t endgame = min(retire, (uint32_t)(kTiles - ENDGAME * ncta));
            while (cur < (uint32_t)kTiles) {
                const size_t off = (size_t)(cur & (kTiles / 2 - 1)) * kUnit;
                const bool pb = cur >= (uint32_t)(kTiles / 2);
                const char* ks = (pb ? k1 : k0) + off;
                const char* vs = (pb ? v1 : v0) + off;
                const uint32_t dst = sb + slot * kSlot, bar = bar_full + 16 * slot;
                mbar_wait(bar_empty + 8 * slot, eph);
                sts32(s_tile + 4 * slot, cur);
                throttle(INFLIGHT);
                mbar_expect_tx(bar, kUnit);
                bulk_g2s(dst, ks, kUnit, bar, pol);
                units++;
                if (cur < endgame) raw = fetch();
                throttle(INFLIGHT);
                mbar_expect_tx(bar + 8, kUnit);
                bulk_g2s(dst + kUnit, vs, kUnit, bar + 8, pol);
                units++;
                if (++slot == NSLOT) { slot = 0; eph ^= 1; }
                if (cur >= endgame) {
                    if (cur >= retire) break;
                    throttle(ENDFETCH);
                    raw = fetch();
                }
                cur = 2 * ncta + (raw & (kTiles - 1));
            }
            const int slot2 = slot + 1 == NSLOT ? 0 : slot + 1;
            mbar_wait(bar_empty + 8 * slot, eph);
            sts32(s_tile + 4 * slot, 0xffffffffu);
            sts64(s_wo, sb + slot * kSlot, sb + slot2 * kSlot);
            sts32(s_owed, cur < (uint32_t)kTiles ? 2u : 0u);
            mbar_arrive(bar_full + 16 * slot);
            if (cur >= (uint32_t)kTiles) asm volatile("red.relaxed.gpu.global.add.u32 [%0], 1;" :: "l"(&g_tile_ctr) : "memory");
            if (cta < kSvcCtas) {
                const char* wsrc = (const char*)P.wo[cta >> 6] + (size_t)(cta & 63) * kWoBytes;
#pragma unroll
                for (int i = 0; i < 4; i++) {
                    if (i == 2) mbar_wait(bar_empty + 8 * slot2, slot2 ? eph : eph ^ 1);
                    if (i < WO_INFLIGHT) throttle(WO_INFLIGHT - i);
                    else mbar_wait(bar_wo + 8 * (i - WO_INFLIGHT), 0);
                    mbar_expect_tx(bar_wo + 8 * i, kWoBytes / 4);
                    bulk_g2s(sb + (i < 2 ? slot : slot2) * kSlot + (i & 1) * kUnit, wsrc + i * (kWoBytes / 4), kWoBytes / 4,
                             bar_wo + 8 * i, pol);
                }
            }
        }
    } else if (warp <= 2) {
        mbar_wait(bar_tag, 0);
        const uint32_t tag = lds32(s_tag);
        const int w = warp - 1;
        const int g = lane >> 2, t = lane & 3;
        const uint32_t koffe = (16 * w + g) * 512 + t * 16 + (g & 1) * 64;
        const uint32_t koffo = (16 * w + g) * 512 + t * 16 - (g & 1) * 64;
        uint32_t voff[4];
        {
            const int mi = lane >> 3, r8 = lane & 7;
            const uint32_t base = kUnit + (16 * w + 8 * (mi >> 1) + r8) * 512 + (mi & 1) * 64;
#pragma unroll
            for (int s = 0; s < 4; s++) voff[s] = base + ((((r8 >> 1) + s) & 3) << 4);
        }
        const bool bsel = (g >> 1) == t;
        float acc[4][4][4];
        uint32_t q[8][4];
        float m = kNegBig, l = 0.f;
#pragma unroll
        for (int j = 0; j < 4; j++)
#pragma unroll
            for (int s = 0; s < 4; s++)
#pragma unroll
                for (int i = 0; i < 4; i++) acc[j][s][i] = 0.f;
#pragma unroll
        for (int r = 0; r < 8; r++) q[r][0] = q[r][1] = q[r][2] = q[r][3] = 0u;

        const uint32_t stage = sb + kOffStage;
        int trig = ((cta >> 3) + 1) * kTilesSeg + 512;
        int seg = -1;
        uint32_t guard = tag;
        int slot = 0; uint32_t ph = 0;
        while (true) {
            mbar_wait(bar_full + 16 * slot, ph);
            const int tile = (int)lds32(s_tile + 4 * slot);
            const int tseg = tile < 0 ? kSegs : (tile >> 11);
            if (tseg != seg) {
                for (int fs = seg < 0 ? 0 : seg; fs < tseg; fs++) {
                    l += __shfl_xor_sync(0xffffffffu, l, 1);
                    l += __shfl_xor_sync(0xffffffffu, l, 2);
                    if (lane == 0 || lane == 4) sts64(s_ml + (g & 1) * 16 + w * 8, __float_as_uint(m * kScaleLog2), __float_as_uint(l));
#pragma unroll
                    for (int j = 0; j < 4; j++)
#pragma unroll
                        for (int i = 0; i < 4; i++) {
                            float r = acc[j][0][i];
#pragma unroll
                            for (int x = 1; x < 4; x++) r += __shfl_sync(0xffffffffu, acc[j][x][i], (lane & ~3) | ((t - x) & 3));
                            sts32f(stage + (w * 512 + (i & 1) * 256 + j * 64 + (i >> 1) * 32 + t * 8 + g) * 4, r);
#pragma unroll
                            for (int x = 0; x < 4; x++) acc[j][x][i] = 0.f;
                        }
                    m = kNegBig; l = 0.f;
                    if (fs >= kSets) {
                        if (fs != seg) guard = ~tag;
                        for (uint32_t spins = 0; !__all_sync(0xffffffffu, guard == tag); spins++) {
                            guard = ld_relaxed1(g_cdone + (fs - kSets) * 8 + (lane & 7));
                            if (spins > kSpinLimit) __trap();
                        }
                    }
                    bar_sync(1, 64);
                    {
                        const uint32_t ptag = seg_tag(fs);
                        const float4 ml = lds128f(s_ml + w * 16);
                        const float M = fmaxf(ml.x, ml.z);
                        const float w0 = ex2(ml.x - M), w1 = ex2(ml.z - M);
                        uint32_t* rec = g_part + ((fs & (kSets - 1)) * kMaxCtas + cta) * kRec;
#pragma unroll
                        for (int u = 0; u < 2; u++) {
                            const float4 a = lds128f(stage + (w * 256 + u * 128 + lane * 4) * 4);
                            const float4 b = lds128f(stage + (512 + w * 256 + u * 128 + lane * 4) * 4);
                            uint4 o;
                            o.x = tagf(a.x * w0 + b.x * w1, ptag); o.y = tagf(a.y * w0 + b.y * w1, ptag);
                            o.z = tagf(a.z * w0 + b.z * w1, ptag); o.w = tagf(a.w * w0 + b.w * w1, ptag);
                            st_relaxed4(rec + w * 256 + u * 128 + lane * 4, o);
                        }
                        if (lane == 0) st_relaxed2(rec + 512 + w * 2, make_uint2(tagf(M, ptag), tagf(ml.y * w0 + ml.w * w1, ptag)));
                    }
                    bar_sync(1, 64);
                }
                if (tile < 0) {
                    if (tid == 32 && trig >= 0) mbar_arrive(bar_svc);
                    break;
                }
                seg = tseg;
                if (seg >= kSets) guard = ld_relaxed1(g_cdone + (seg - kSets) * 8 + (lane & 7));
                mbar_wait(bar_q + (seg ? 8 : 0), 0);
#pragma unroll
                for (int r = 0; r < 8; r++) {
                    const uint4 v = lds128(sb + kOffQ + seg * 1024 + (g & 1) * 512 + r * 64 + t * 16);
                    q[r][0] = v.x; q[r][1] = v.y; q[r][2] = v.z; q[r][3] = v.w;
                }
            }
            if (tile >= trig && trig >= 0) {
                if (tid == 32) mbar_arrive(bar_svc);
                trig = -1;
            }
            const uint32_t base = sb + slot * kSlot;
            float s0a[4] = {0.f, 0.f, 0.f, 0.f}, s0b[4] = {0.f, 0.f, 0.f, 0.f};
            float s1a[4] = {0.f, 0.f, 0.f, 0.f}, s1b[4] = {0.f, 0.f, 0.f, 0.f};
#pragma unroll
            for (int r = 0; r < 8; r++) {
                const uint32_t ko = base + ((r & 1) ? koffo : koffe) + r * 64;
                const uint4 ka = lds128(ko);
                const uint4 kb = lds128(ko + 4096);
                mma16816(s0a, q[r][0], q[r ^ 1][0], q[r][1], q[r ^ 1][1], ka.x, ka.y);
                mma16816(s0b, q[r][2], q[r ^ 1][2], q[r][3], q[r ^ 1][3], ka.z, ka.w);
                mma16816(s1a, q[r][0], q[r ^ 1][0], q[r][1], q[r ^ 1][1], kb.x, kb.y);
                mma16816(s1b, q[r][2], q[r ^ 1][2], q[r][3], q[r ^ 1][3], kb.z, kb.w);
            }
            const float s00 = s0a[0] + s0b[0], s01 = s0a[3] + s0b[3];
            const float s10 = s1a[0] + s1b[0], s11 = s1a[3] + s1b[3];
            float mx = fmaxf(fmaxf(s00, s01), fmaxf(s10, s11));
            mx = fmaxf(mx, __shfl_xor_sync(0xffffffffu, mx, 1));
            mx = fmaxf(mx, __shfl_xor_sync(0xffffffffu, mx, 2));
            if (__any_sync(0xffffffffu, mx > m)) {
                const float mn = fmaxf(m, mx);
                const float al = ex2((m - mn) * kScaleLog2);
                const float ao = __shfl_xor_sync(0xffffffffu, al, 4);
                const float a0 = (g & 1) ? ao : al, a1 = (g & 1) ? al : ao;
                m = mn; l *= al;
#pragma unroll
                for (int j = 0; j < 4; j++)
#pragma unroll
                    for (int s = 0; s < 4; s++) {
                        acc[j][s][0] *= a0; acc[j][s][1] *= a1; acc[j][s][2] *= a0; acc[j][s][3] *= a1;
                    }
            }
            const float mc = m * kScaleLog2;
            const float p00 = ex2(fmaf(s00, kScaleLog2, -mc)), p01 = ex2(fmaf(s01, kScaleLog2, -mc));
            const float p10 = ex2(fmaf(s10, kScaleLog2, -mc)), p11 = ex2(fmaf(s11, kScaleLog2, -mc));
            l += (p00 + p01) + (p10 + p11);
            const uint32_t b0 = bsel ? pack_bf16(p00, p01) : 0u;
            const uint32_t b1 = bsel ? pack_bf16(p10, p11) : 0u;
            mbar_wait(bar_full + 16 * slot + 8, ph);
#pragma unroll
            for (int j = 0; j < 4; j++)
#pragma unroll
                for (int s = 0; s < 4; s++) {
                    uint32_t a0, a1, a2, a3;
                    ldsm4t(base + voff[s] + j * 128, a0, a1, a2, a3);
                    mma16816(acc[j][s], a0, a1, a2, a3, b0, b1);
                }
            __syncwarp();
            if (lane == 0) mbar_arrive(bar_empty + 8 * slot);
            if (++slot == NSLOT) { slot = 0; ph ^= 1; }
        }
    } else {
        uint32_t tag;
        const int st = tid - 96, sw = st >> 5;
        const uint32_t s_red = sb + kOffRed;
        const uint32_t s_ML  = sb + kOffML;
        if (cta < kSvcCtas) {
            const int p = cta >> 6;
            const int r8 = st >> 3, u = st & 7;
            const uint4* wp = (const uint4*)(P.wq[p] + (size_t)r8 * kHD + (cta & 63) * 64 + u * 8);
            const __nv_bfloat16* xp = P.x[p] + r8;
            uint4 wv[14]; float xv[14];
#pragma unroll
            for (int i = 0; i < 14; i++) {
                asm volatile("ld.global.nc.L1::no_allocate.v4.u32 {%0,%1,%2,%3}, [%4];"
                             : "=r"(wv[i].x), "=r"(wv[i].y), "=r"(wv[i].z), "=r"(wv[i].w) : "l"(wp + (size_t)i * 32 * (kHD / 8)));
            }
#pragma unroll
            for (int i = 0; i < 14; i++) xv[i] = __bfloat162float(xp[i * 32]);
            float a[8];
#pragma unroll
            for (int e = 0; e < 8; e++) a[e] = 0.f;
#pragma unroll
            for (int i = 0; i < 14; i++) {
                a[0] = fmaf(xv[i], bf_lo(wv[i].x), a[0]); a[1] = fmaf(xv[i], bf_hi(wv[i].x), a[1]);
                a[2] = fmaf(xv[i], bf_lo(wv[i].y), a[2]); a[3] = fmaf(xv[i], bf_hi(wv[i].y), a[3]);
                a[4] = fmaf(xv[i], bf_lo(wv[i].z), a[4]); a[5] = fmaf(xv[i], bf_hi(wv[i].z), a[5]);
                a[6] = fmaf(xv[i], bf_lo(wv[i].w), a[6]); a[7] = fmaf(xv[i], bf_hi(wv[i].w), a[7]);
            }
#pragma unroll
            for (int e = 0; e < 8; e++) {
                a[e] += __shfl_xor_sync(0xffffffffu, a[e], 8);
                a[e] += __shfl_xor_sync(0xffffffffu, a[e], 16);
            }
            if (lane < 8) {
                sts128f(s_red + (sw * 72 + lane * 8) * 4, make_float4(a[0], a[1], a[2], a[3]));
                sts128f(s_red + (sw * 72 + lane * 8 + 4) * 4, make_float4(a[4], a[5], a[6], a[7]));
            }
            mbar_wait(bar_tag, 0);
            tag = lds32(s_tag);
            bar_sync(2, kSvcThreads);
            if (st == 0) TL(8);
            if (st < 32) {
                float s0 = 0.f, s1 = 0.f;
#pragma unroll
                for (int i = 0; i < 8; i++) { const float2 v = lds64f(s_red + (i * 72 + st * 2) * 4); s0 += v.x; s1 += v.y; }
                const uint32_t pk = pack_bf16(s0, s1);
                st_relaxed2(g_q + cta * 64 + st * 2, make_uint2((pk << 16) | tag, (pk & 0xffff0000u) | tag));
            }
        } else {
            mbar_wait(bar_tag, 0);
            tag = lds32(s_tag);
        }
        {
            if (st < 128) {
                uint4 v = make_uint4(~tag, ~tag, ~tag, ~tag);
                for (uint32_t spins = 0;; spins++) {
                    uint32_t bad = 0;
                    repoll4(v, g_q + st * 4, tag, bad);
                    if (!bad) break;
                    if (spins > kSpinLimit) __trap();
                }
                sts64(sb + kOffQ + st * 8, __byte_perm(v.x, v.y, 0x7632), __byte_perm(v.z, v.w, 0x7632));
                __syncwarp();
                if (lane == 0) mbar_arrive(bar_q);
            }
            if (QDELAY) { if (lane == 0) { mbar_wait(bar_q, 0); __nanosleep(QDELAY); } __syncwarp(); }
            uint4 v[8];
#pragma unroll
            for (int i = 0; i < 8; i++) v[i] = make_uint4(~tag, ~tag, ~tag, ~tag);
            for (uint32_t spins = 0;; spins++) {
                uint32_t bad = 0;
#pragma unroll
                for (int i = 0; i < 8; i++) repoll4(v[i], g_q + (i * 256 + st) * 4, tag, bad);
                if (!bad) break;
                if (spins > kSpinLimit) __trap();
            }
#pragma unroll
            for (int i = 0; i < 8; i++) {
                if (i > 0 || st >= 128)
                    sts64(sb + kOffQ + (i * 256 + st) * 8, __byte_perm(v[i].x, v[i].y, 0x7632), __byte_perm(v[i].z, v[i].w, 0x7632));
            }
            __syncwarp();
            if (lane == 0) mbar_arrive(bar_q + 8);
        }
        if (cta >= kSvcCtas) return;

        const int sg = cta >> 3;
        const bool early = sg == kSegs - 1;
        const uint32_t ptag = seg_tag(sg);
        const int g = lane >> 2, t = lane & 3;
        const int i16 = st >> 4, u = st & 15;
        const uint32_t* po  = g_part + ((sg & (kSets - 1)) * kMaxCtas + i16) * kRec + (cta & 7) * 64 + u * 4;
        const uint32_t* pml = g_part + ((sg & (kSets - 1)) * kMaxCtas + i16 + 16 * u) * kRec + 512 + ((cta >> 2) & 1) * 2;
        uint32_t woff[4];
#pragma unroll
        for (int s = 0; s < 4; s++)
            woff[s] = (2 * (lane & 7) + (lane >> 4)) * (kD * 2) + sw * 128 + ((((lane & 7) + s + ((lane >> 3) & 1) * 4) & 7) << 4);
#pragma unroll 1
        for (int pass = WARMUP ? 0 : 1; pass < 2; pass++) {
            const uint32_t live = pass;
            uint32_t wa[4][4][4];
            auto load_wo = [&](int kb) {
                if (live) mbar_wait(bar_wo + 8 * kb, 0);
                const uint32_t wb = lds32(s_wo + (kb >> 1) * 4) + (kb & 1) * kUnit;
#pragma unroll
                for (int s = 0; s < 4; s++) ldsm4t(wb + woff[s], wa[kb][s][0], wa[kb][s][1], wa[kb][s][2], wa[kb][s][3]);
            };
            if (st == 0 && live) { mbar_wait(bar_svc, 0); TL(4); }
            bar_sync(2, kSvcThreads);
            if (early && sw < 7) {
#pragma unroll
                for (int kb = 0; kb < 4; kb++) load_wo(kb);
            }
            {
                uint4 ov[9];
                uint2 ml = make_uint2(tagf(kNegBig * kScaleLog2, ptag ^ ((u < 9 && i16 + 16 * u < ncta) ? live : 0u)), ptag);
#pragma unroll
                for (int k = 0; k < 9; k++) {
                    const uint32_t z = ptag ^ ((i16 + 16 * k < ncta) ? live : 0u);
                    ov[k] = make_uint4(z, z, z, z);
                }
                for (uint32_t spins = 0;; spins++) {
                    uint32_t bad = 0;
                    repoll2(ml, pml, ptag, bad);
#pragma unroll
                    for (int k = 0; k < 9; k++) repoll4(ov[k], po + k * 16 * kRec, ptag, bad);
                    if (!__any_sync(0xffffffffu, bad)) break;
                    if (spins > kSpinLimit) __trap();
                }
                if (early && lane == 0 && live) TLMAX(13);
                const float M = warp_max(asf(ml.x));
                const float wgt = ex2(asf(ml.x) - M);
                float L = wgt * asf(ml.y);
                float4 a = make_float4(0.f, 0.f, 0.f, 0.f), c = make_float4(0.f, 0.f, 0.f, 0.f);
#pragma unroll
                for (int k = 0; k < 9; k++) {
                    if ((k & 1) == 0 && k < 8) L += __shfl_xor_sync(0xffffffffu, L, 1 << (k >> 1));
                    const float wk = __shfl_sync(0xffffffffu, wgt, (lane & 16) | k);
                    float4& y = (k & 1) ? c : a;
                    y.x = fmaf(wk, asf(ov[k].x), y.x); y.y = fmaf(wk, asf(ov[k].y), y.y);
                    y.z = fmaf(wk, asf(ov[k].z), y.z); y.w = fmaf(wk, asf(ov[k].w), y.w);
                }
                a.x += c.x; a.y += c.y; a.z += c.z; a.w += c.w;
                a.x += __shfl_xor_sync(0xffffffffu, a.x, 16); a.y += __shfl_xor_sync(0xffffffffu, a.y, 16);
                a.z += __shfl_xor_sync(0xffffffffu, a.z, 16); a.w += __shfl_xor_sync(0xffffffffu, a.w, 16);
                if (lane < 16) sts128f(s_red + (sw * 72 + lane * 4 + (lane & 8)) * 4, a);
                if (u == 0) { sts32f(s_ML + sw * 4, M); sts32f(s_ML + 32 + i16 * 4, L); }
            }
            bar_sync(2, kSvcThreads);
            if (sw < 7) {
                const float4 ma = lds128f(s_ML), mb = lds128f(s_ML + 16);
                float2 ow[8];
#pragma unroll
                for (int i = 0; i < 8; i++) ow[i] = lds64f(s_red + (i * 72 + 16 * t + 2 * g + (t & 2) * 4) * 4);
                const float4 l0 = lds128f(s_ML + 32), l1 = lds128f(s_ML + 48), l2 = lds128f(s_ML + 64), l3 = lds128f(s_ML + 80);
                const float Mt = fmaxf(fmaxf(fmaxf(ma.x, ma.y), fmaxf(ma.z, ma.w)), fmaxf(fmaxf(mb.x, mb.y), fmaxf(mb.z, mb.w)));
                const float e[8] = {ex2(ma.x - Mt), ex2(ma.y - Mt), ex2(ma.z - Mt), ex2(ma.w - Mt),
                                    ex2(mb.x - Mt), ex2(mb.y - Mt), ex2(mb.z - Mt), ex2(mb.w - Mt)};
                const float o0 = (fmaf(e[0], ow[0].x, e[1] * ow[1].x) + fmaf(e[2], ow[2].x, e[3] * ow[3].x))
                               + (fmaf(e[4], ow[4].x, e[5] * ow[5].x) + fmaf(e[6], ow[6].x, e[7] * ow[7].x));
                const float o1 = (fmaf(e[0], ow[0].y, e[1] * ow[1].y) + fmaf(e[2], ow[2].y, e[3] * ow[3].y))
                               + (fmaf(e[4], ow[4].y, e[5] * ow[5].y) + fmaf(e[6], ow[6].y, e[7] * ow[7].y));
                const float Lt = (fmaf(e[0], l0.x + l0.y, e[1] * (l0.z + l0.w)) + fmaf(e[2], l1.x + l1.y, e[3] * (l1.z + l1.w)))
                               + (fmaf(e[4], l2.x + l2.y, e[5] * (l2.z + l2.w)) + fmaf(e[6], l3.x + l3.y, e[7] * (l3.z + l3.w)));
                const float inv = rcp(Lt);
                const uint32_t pk = pack_bf16(o0, o1);
                const uint32_t sel0 = ((g >> 1) == t) ? ((g & 1) ? 0x1044u : 0x4410u) : 0x4444u;
                const uint32_t sel1 = ((g >> 1) == t) ? ((g & 1) ? 0x3244u : 0x4432u) : 0x4444u;
                uint32_t b0[4], b1[4];
#pragma unroll
                for (int kb = 0; kb < 4; kb++) {
                    const uint32_t v = __shfl_sync(0xffffffffu, pk, (lane & ~3) | kb);
                    b0[kb] = __byte_perm(v, 0u, sel0);
                    b1[kb] = __byte_perm(v, 0u, sel1);
                }
                float d[4][4], f[4][4];
#pragma unroll
                for (int s = 0; s < 4; s++) { d[s][0] = d[s][1] = d[s][2] = d[s][3] = 0.f; f[s][0] = f[s][1] = f[s][2] = f[s][3] = 0.f; }
                if (early) {
#pragma unroll
                    for (int kb = 0; kb < 4; kb++)
#pragma unroll
                        for (int s = 0; s < 4; s++)
                            mma16816((kb & 1) ? f[s] : d[s], wa[kb][s][0], wa[kb][s][1], wa[kb][s][2], wa[kb][s][3], b0[kb], b1[kb]);
                } else {
                    if (lane == 0 && live) mbar_wait(bar_wo, 0);
                    __syncwarp();
#pragma unroll
                    for (int kb = 0; kb < 4; kb++) {
                        load_wo(kb);
#pragma unroll
                        for (int s = 0; s < 4; s++)
                            mma16816((kb & 1) ? f[s] : d[s], wa[kb][s][0], wa[kb][s][1], wa[kb][s][2], wa[kb][s][3], b0[kb], b1[kb]);
                    }
                }
                float uu[8];
#pragma unroll
                for (int x = 0; x < 8; x++) {
                    const int y = (x + 7) & 7;
                    uu[x] = (d[x & 3][(x >> 2) * 2] + d[y & 3][(y >> 2) * 2 + 1]) + (f[x & 3][(x >> 2) * 2] + f[y & 3][(y >> 2) * 2 + 1]);
                }
#pragma unroll
                for (int y = 1; y < 4; y++) {
                    uu[2 * y]     = __shfl_sync(0xffffffffu, uu[2 * y], (lane & ~3) | ((t - y) & 3));
                    uu[2 * y + 1] = __shfl_sync(0xffffffffu, uu[2 * y + 1], (lane & ~3) | ((t - y) & 3));
                }
                const float r0 = ((uu[0] + uu[2]) + (uu[4] + uu[6])) * inv, r1 = ((uu[1] + uu[3]) + (uu[5] + uu[7])) * inv;
                if (live) st_relaxed2(g_out_part + cta * kD + sw * 64 + lane * 2, make_uint2(tagf(r0, tag), tagf(r1, tag)));
            } else {
                if (lane == 0 && live) {
                    st_relaxed1(g_cdone + cta, tag);
                    if (early) {
                        const uint32_t owed = lds32(s_owed);
                        if (owed) asm volatile("red.relaxed.gpu.global.add.u32 [%0], %1;" :: "l"(&g_tile_ctr), "r"(owed) : "memory");
                    }
                    TL(5);
                }
                if (cta < 112) {
                    const int fp = cta >= 56 ? 1 : 0, fc = cta - 56 * fp;
                    const uint32_t* src = g_out_part + (fp * 64 + (lane >> 1)) * kD + fc * 8 + (lane & 1) * 4;
                    const int j = ((lane >> 4) & 1) | (((lane >> 3) & 1) << 1) | ((lane & 1) << 2);
                    __nv_bfloat16* dst = P.out + fp * kD + (fc >> 3) * 64 + 16 * (j >> 1) + 8 * (j & 1) + (fc & 7);
                    if (lane == 0 && live) { mbar_wait(bar_wo, 0); mbar_wait(bar_wo + 24, 0); }
                    __syncwarp();
                    const uint32_t z = tag ^ live;
                    uint4 v[4];
#pragma unroll
                    for (int i = 0; i < 4; i++) v[i] = make_uint4(z, z, z, z);
                    for (uint32_t spins = 0;; spins++) {
                        uint32_t bad = 0;
#pragma unroll
                        for (int i = 0; i < 4; i++) repoll4(v[i], src + i * 16 * kD, tag, bad);
                        if (!__any_sync(0xffffffffu, bad)) break;
                        if (spins > kSpinLimit) __trap();
                    }
                    if (lane == 0 && live) TLMAX(fp ? 48 : 49);
                    const float ax = (asf(v[0].x) + asf(v[1].x)) + (asf(v[2].x) + asf(v[3].x));
                    const float ay = (asf(v[0].y) + asf(v[1].y)) + (asf(v[2].y) + asf(v[3].y));
                    const float az = (asf(v[0].z) + asf(v[1].z)) + (asf(v[2].z) + asf(v[3].z));
                    const float aw = (asf(v[0].w) + asf(v[1].w)) + (asf(v[2].w) + asf(v[3].w));
                    const bool h4 = lane & 16, h3 = lane & 8;
                    float b0 = (h4 ? ay : ax) + __shfl_xor_sync(0xffffffffu, h4 ? ax : ay, 16);
                    float b1 = (h4 ? aw : az) + __shfl_xor_sync(0xffffffffu, h4 ? az : aw, 16);
                    float r = (h3 ? b1 : b0) + __shfl_xor_sync(0xffffffffu, h3 ? b0 : b1, 8);
                    r += __shfl_xor_sync(0xffffffffu, r, 4);
                    r += __shfl_xor_sync(0xffffffffu, r, 2);
                    if (live && (lane & 6) == 0) *dst = __float2bfloat16(r);
                }
            }
        }
    }
}

}

extern "C" void kernel_launch(void* const* d_in, const int* in_sizes, int n_in, void* d_out, int out_size) {
    (void)in_sizes; (void)n_in; (void)out_size;
    static int grid = 0;
    if (grid == 0) {
        int dev = 0, sms = 0;
        cudaGetDevice(&dev);
        cudaDeviceGetAttribute(&sms, cudaDevAttrMultiProcessorCount, dev);
        cudaFuncSetAttribute(gqa_decode_kernel, cudaFuncAttributeMaxDynamicSharedMemorySize, (int)kSmemBytes);
        grid = sms < kMaxCtas ? sms : kMaxCtas;
    }
    Params P;
    for (int p = 0; p < 2; p++) {
        P.x[p]  = (const __nv_bfloat16*)d_in[5 * p + 0];
        P.k[p]  = (const char*)d_in[5 * p + 1];
        P.v[p]  = (const char*)d_in[5 * p + 2];
        P.wq[p] = (const __nv_bfloat16*)d_in[5 * p + 3];
        P.wo[p] = (const __nv_bfloat16*)d_in[5 * p + 4];
    }
    P.out = (__nv_bfloat16*)d_out;
    gqa_decode_kernel<<<grid, kThreads, kSmemBytes, cudaStreamPerThread>>>(P);
}
```

```cpp
#include <cuda_runtime.h>
#include <cuda_bf16.h>
#include <cuda.h>
#include <stdint.h>

namespace {

constexpr int kD        = 448;
constexpr int kHD       = 4096;
constexpr int kSegs     = 16;
constexpr int kTilesSeg = 2048;
constexpr int kTiles    = kSegs * kTilesSeg;
constexpr int kRoles    = 14;
constexpr int kMaxCtas  = 120;
constexpr int kCntSeg   = 2;
constexpr int kRetire   = 4;
constexpr int NSLOT     = 6;

constexpr int kThreads    = 384;
constexpr int kSvcThreads = 256;

constexpr uint32_t kUnit     = 16384;
constexpr uint32_t kSlot     = 2 * kUnit;
constexpr uint32_t kInbox    = 16 * 256 + 16 * 8;
constexpr uint32_t kOffWq    = (NSLOT - 2) * kSlot;
constexpr uint32_t kOffQ     = NSLOT * kSlot;
constexpr uint32_t kOffInbox = kOffQ + 16384;
constexpr uint32_t kOffRed   = kOffInbox + 2 * kInbox;
constexpr uint32_t kOffOut   = kOffRed + 8 * 72 * 4;
constexpr uint32_t kOffMisc  = kOffOut + 2048;
constexpr uint32_t kSmemBytes = kOffMisc + 640;

constexpr float kScaleLog2 = 0.0625f * 1.4426950408889634f;
constexpr float kNegBig    = -3.0e38f;

struct Params {
    const char* k0;
    const char* v0;
    unsigned int* ctr;
    uint32_t* q;
    const __nv_bfloat16* x[2];
    const char* k1;
    const char* v1;
    __nv_bfloat16* out;
    uint32_t* rec;
    uint32_t* cnt;
};
struct Maps {
    CUtensorMap wq[2];
    CUtensorMap wo[2];
};

constexpr int kRec = 96;
__device__ unsigned int g_tile_ctr;
__device__ __align__(128) uint32_t g_q[2 * kHD];
__device__ __align__(128) uint32_t g_cnt[128];
__device__ __align__(128) uint32_t g_rec[kSegs * kMaxCtas * kRec];

constexpr uint32_t kSpinLimit = 1u << 22;
__device__ __forceinline__ uint32_t smem_u32(const void* p) { return (uint32_t)__cvta_generic_to_shared(p); }
__device__ __forceinline__ void mbar_init(uint32_t bar, uint32_t cnt) {
    asm volatile("mbarrier.init.shared::cta.b64 [%0], %1;" :: "r"(bar), "r"(cnt) : "memory");
}
__device__ __forceinline__ void mbar_expect_tx(uint32_t bar, uint32_t bytes) {
    asm volatile("mbarrier.arrive.expect_tx.shared::cta.b64 _, [%0], %1;" :: "r"(bar), "r"(bytes) : "memory");
}
__device__ __forceinline__ void mbar_arrive(uint32_t bar) {
    asm volatile("mbarrier.arrive.shared::cta.b64 _, [%0];" :: "r"(bar) : "memory");
}
__device__ __forceinline__ void mbar_wait(uint32_t bar, uint32_t parity) {
    uint32_t ok;
    uint32_t spins = 0;
    while (true) {
        asm volatile("{\n.reg .pred p;\nmbarrier.try_wait.parity.shared::cta.b64 p, [%1], %2;\nselp.u32 %0, 1, 0, p;\n}"
                     : "=r"(ok) : "r"(bar), "r"(parity) : "memory");
        if (ok) break;
        if (++spins > kSpinLimit) __trap();
    }
}
__device__ __forceinline__ void bulk_g2s(uint32_t dst, const void* src, uint32_t bytes, uint32_t bar, uint64_t pol) {
    asm volatile("cp.async.bulk.shared::cluster.global.mbarrier::complete_tx::bytes.L2::cache_hint [%0], [%1], %2, [%3], %4;"
                 :: "r"(dst), "l"(src), "r"(bytes), "r"(bar), "l"(pol) : "memory");
}
__device__ __forceinline__ void tma2d(uint32_t dst, const CUtensorMap* map, int c0, int c1, uint32_t bar, uint64_t pol) {
    asm volatile("cp.async.bulk.tensor.2d.shared::cluster.global.mbarrier::complete_tx::bytes.L2::cache_hint "
                 "[%0], [%1, {%3, %4}], [%2], %5;"
                 :: "r"(dst), "l"(map), "r"(bar), "r"(c0), "r"(c1), "l"(pol) : "memory");
}
__device__ __forceinline__ void st_relaxed2(void* p, uint2 v) {
    asm volatile("st.relaxed.gpu.global.v2.u32 [%0], {%1,%2};" :: "l"(p), "r"(v.x), "r"(v.y) : "memory");
}
__device__ __forceinline__ uint32_t tagf(float v, uint32_t tag) { return (__float_as_uint(v) & ~1u) | tag; }
__device__ __forceinline__ void repoll4(uint4& v, const void* p, uint32_t tag, uint32_t& bad) {
    asm volatile("{\n.reg .pred p;\n.reg .b32 a, b;\n"
                 "lop3.b32 a, %0, %1, %5, 0x7E;\nlop3.b32 b, %2, %3, %5, 0x7E;\nlop3.b32 a, a, b, 1, 0xA8;\n"
                 "setp.ne.u32 p, a, 0;\n"
                 "@p ld.relaxed.gpu.global.v4.u32 {%0,%1,%2,%3}, [%6];\n"
                 "or.b32 %4, %4, a;\n}"
                 : "+r"(v.x), "+r"(v.y), "+r"(v.z), "+r"(v.w), "+r"(bad) : "r"(tag), "l"(p) : "memory");
}
__device__ __forceinline__ uint32_t repoll2(uint2& v, const void* p, uint32_t tag) {
    uint32_t bad;
    asm volatile("{\n.reg .pred p;\n"
                 "lop3.b32 %2, %0, %1, %3, 0x7E;\nand.b32 %2, %2, 1;\n"
                 "setp.ne.u32 p, %2, 0;\n"
                 "@p ld.relaxed.gpu.global.v2.u32 {%0,%1}, [%4];\n}"
                 : "+r"(v.x), "+r"(v.y), "=&r"(bad) : "r"(tag), "l"(p) : "memory");
    return bad;
}
__device__ __forceinline__ uint32_t repoll_ml(uint2& v, const void* p, uint32_t tag) {
    uint32_t bad;
    asm volatile("{\n.reg .pred p;\n.reg .b64 w;\n"
                 "lop3.b32 %2, %1, %3, 1, 0x28;\n"
                 "setp.ne.u32 p, %2, 0;\nmov.b64 w, {%0,%1};\n"
                 "@p ld.relaxed.gpu.global.b64 w, [%4];\nmov.b64 {%0,%1}, w;\n}"
                 : "+r"(v.x), "+r"(v.y), "=&r"(bad) : "r"(tag), "l"(p) : "memory");
    return bad;
}
__device__ __forceinline__ void st_relaxed64(void* p, uint32_t lo, uint32_t hi) {
    asm volatile("{\n.reg .b64 w;\nmov.b64 w, {%1,%2};\nst.relaxed.gpu.global.b64 [%0], w;\n}" :: "l"(p), "r"(lo), "r"(hi) : "memory");
}
__device__ __forceinline__ uint32_t or3(uint32_t a, uint32_t b, uint32_t c) {
    uint32_t r; asm("lop3.b32 %0, %1, %2, %3, 0xFE;" : "=r"(r) : "r"(a), "r"(b), "r"(c)); return r;
}
__device__ __forceinline__ void bar_sync(int id, int n) { asm volatile("bar.sync %0, %1;" :: "r"(id), "r"(n) : "memory"); }
__device__ __forceinline__ uint4 lds128(uint32_t a) {
    uint4 v;
    asm volatile("ld.shared.v4.u32 {%0,%1,%2,%3}, [%4];" : "=r"(v.x), "=r"(v.y), "=r"(v.z), "=r"(v.w) : "r"(a) : "memory");
    return v;
}
__device__ __forceinline__ float2 lds64f(uint32_t a) {
    float2 v;
    asm volatile("ld.shared.v2.f32 {%0,%1}, [%2];" : "=f"(v.x), "=f"(v.y) : "r"(a) : "memory");
    return v;
}
__device__ __forceinline__ uint32_t lds32(uint32_t a) {
    uint32_t v;
    asm volatile("ld.shared.u32 %0, [%1];" : "=r"(v) : "r"(a) : "memory");
    return v;
}
__device__ __forceinline__ void sts128f(uint32_t a, float4 v) {
    asm volatile("st.shared.v4.f32 [%0], {%1,%2,%3,%4};" :: "r"(a), "f"(v.x), "f"(v.y), "f"(v.z), "f"(v.w) : "memory");
}
__device__ __forceinline__ void sts64(uint32_t a, uint32_t x, uint32_t y) {
    asm volatile("st.shared.v2.u32 [%0], {%1,%2};" :: "r"(a), "r"(x), "r"(y) : "memory");
}
__device__ __forceinline__ void sts32(uint32_t a, uint32_t v) {
    asm volatile("st.shared.u32 [%0], %1;" :: "r"(a), "r"(v) : "memory");
}
__device__ __forceinline__ void sts32f(uint32_t a, float v) { sts32(a, __float_as_uint(v)); }
__device__ __forceinline__ void ldsm4t(uint32_t a, uint32_t& r0, uint32_t& r1, uint32_t& r2, uint32_t& r3) {
    asm volatile("ldmatrix.sync.aligned.m8n8.x4.trans.shared.b16 {%0,%1,%2,%3}, [%4];"
                 : "=r"(r0), "=r"(r1), "=r"(r2), "=r"(r3) : "r"(a) : "memory");
}
__device__ __forceinline__ void mma16816(float (&d)[4], uint32_t a0, uint32_t a1, uint32_t a2, uint32_t a3, uint32_t b0, uint32_t b1) {
    asm volatile("mma.sync.aligned.m16n8k16.row.col.f32.bf16.bf16.f32 {%0,%1,%2,%3}, {%4,%5,%6,%7}, {%8,%9}, {%0,%1,%2,%3};"
                 : "+f"(d[0]), "+f"(d[1]), "+f"(d[2]), "+f"(d[3])
                 : "r"(a0), "r"(a1), "r"(a2), "r"(a3), "r"(b0), "r"(b1));
}
__device__ __forceinline__ float ex2(float x) { float y; asm("ex2.approx.ftz.f32 %0, %1;" : "=f"(y) : "f"(x)); return y; }
__device__ __forceinline__ float rcp(float x) { float y; asm("rcp.approx.ftz.f32 %0, %1;" : "=f"(y) : "f"(x)); return y; }
__device__ __forceinline__ uint32_t pack_bf16(float lo, float hi) {
    uint32_t r; asm("cvt.rn.bf16x2.f32 %0, %1, %2;" : "=r"(r) : "f"(hi), "f"(lo)); return r;
}
__device__ __forceinline__ float bf_lo(uint32_t u) { return __uint_as_float(u << 16); }
__device__ __forceinline__ float bf_hi(uint32_t u) { return __uint_as_float(u & 0xffff0000u); }
__device__ __forceinline__ float asf(uint32_t u) { return __uint_as_float(u); }
__device__ __forceinline__ float warp_max(float v) {
    int i = __float_as_int(v);
    i ^= (i >> 31) & 0x7fffffff;
    i = __reduce_max_sync(0xffffffffu, i);
    i ^= (i >> 31) & 0x7fffffff;
    return __int_as_float(i);
}
__device__ __forceinline__ uint32_t mapa(uint32_t a, uint32_t rank) {
    uint32_t r; asm("mapa.shared::cluster.u32 %0, %1, %2;" : "=r"(r) : "r"(a), "r"(rank)); return r;
}
__device__ __forceinline__ void st_async2(uint32_t a, float x, float y, uint32_t bar) {
    asm volatile("st.async.weak.shared::cluster.mbarrier::complete_tx::bytes.v2.f32 [%0], {%1,%2}, [%3];" :: "r"(a), "f"(x), "f"(y), "r"(bar) : "memory");
}
__device__ __forceinline__ void store_q(uint32_t qbase, int n, uint4 v) {
    const uint32_t a = qbase + (n >> 4) * 128 + (n & 1) * 64 + ((n >> 1) & 3) * 16 + ((n >> 3) & 1) * 4;
    sts32(a, __byte_perm(v.x, v.y, 0x7632));
    sts32(a + 8, __byte_perm(v.z, v.w, 0x7632));
}
__device__ __forceinline__ uint32_t ctr_fetch(unsigned int* p) {
    uint32_t r;
    asm volatile("atom.relaxed.gpu.global.inc.u32 %0, [%1], 0xffff;" : "=r"(r) : "l"(p) : "memory");
    return r;
}
__device__ __forceinline__ void ctr_inc(unsigned int* p) {
    asm volatile("red.relaxed.gpu.global.inc.u32 [%0], 0xffff;" :: "l"(p) : "memory");
}
__device__ __forceinline__ void sleep_us(int n) { for (int i = 0; i < n; i++) __nanosleep(1000); }
__device__ __forceinline__ void cluster_wait() { asm volatile("barrier.cluster.wait.aligned;" ::: "memory"); }

template <int kClusters>
__global__ void __cluster_dims__(8, 1, 1) __launch_bounds__(kThreads, 1)
gqa_decode_kernel(const __grid_constant__ Params P, const __grid_constant__ Maps M) {
    constexpr int kCtas = kClusters * 8;
    extern __shared__ __align__(1024) unsigned char smem[];
    const uint32_t sb = smem_u32(smem);
    const uint32_t bar_full  = sb + kOffMisc;
    const uint32_t bar_empty = bar_full + 16 * NSLOT;
    const uint32_t bar_wo    = bar_empty + 8 * NSLOT;
    const uint32_t bar_role  = bar_wo + 64;
    const uint32_t bar_q     = bar_role + 8;
    const uint32_t bar_tag   = bar_q + 16;
    const uint32_t bar_free  = bar_tag + 8;
    const uint32_t bar_out   = bar_free + 16;
    const uint32_t bar_inbox = bar_out + 8;
    const uint32_t bar_wq    = bar_inbox + 8 * kSegs;
    const uint32_t bar_wqfree = bar_wq + 8;
    const uint32_t bar_red   = bar_wqfree + 8;
    const uint32_t bar_go    = bar_red + 8;
    const uint32_t s_seg     = sb + kOffMisc + 512;
    const uint32_t s_tag     = sb + kOffMisc + 576;
    const uint32_t s_wo      = sb + kOffMisc + 584;
    const uint32_t s_role    = sb + kOffMisc + 596;
    const uint32_t s_retire  = sb + kOffMisc + 592;

    const int tid = threadIdx.x, warp = tid >> 5, lane = tid & 31;
    const int cta = blockIdx.x, rank = cta & 7;

    auto load_wq = [&](int slice, uint64_t policy) {
        mbar_expect_tx(bar_wq, kD * 128 + kD * 2);
        bulk_g2s(sb + kOffWq + kD * 128, P.x[slice >> 6], kD * 2, bar_wq, policy);
        tma2d(sb + kOffWq, &M.wq[slice >> 6], (slice & 63) * 64, 0, bar_wq, policy);
        tma2d(sb + kOffWq + kD * 64, &M.wq[slice >> 6], (slice & 63) * 64, kD / 2, bar_wq, policy);
    };
    uint64_t pol = 0;
    uint32_t raw = 0;
    if (tid == 0) {
        asm volatile("createpolicy.fractional.L2::evict_first.b64 %0, 1.0;" : "=l"(pol));
        mbar_init(bar_full, 1);
        asm volatile("fence.mbarrier_init.release.cluster;" ::: "memory");
        bulk_g2s(sb, P.k0 + (size_t)cta * kUnit, kUnit, bar_full, pol);
        raw = ctr_fetch(P.ctr);
        mbar_init(bar_wq, 1);
        mbar_init(bar_full + 8, 1);
        mbar_init(bar_full + 16, 1);
        mbar_init(bar_full + 24, 1);
        asm volatile("fence.mbarrier_init.release.cluster;" ::: "memory");
        load_wq(cta, pol);
        bulk_g2s(sb + kUnit, P.v0 + (size_t)cta * kUnit, kUnit, bar_full + 8, pol);
        bulk_g2s(sb + kSlot, P.k0 + (size_t)(kCtas + cta) * kUnit, kUnit, bar_full + 16, pol);
        bulk_g2s(sb + kSlot + kUnit, P.v0 + (size_t)(kCtas + cta) * kUnit, kUnit, bar_full + 24, pol);
        for (int i = 0; i < 4; i++) mbar_expect_tx(bar_full + 8 * i, kUnit);
    }
    asm volatile("" ::: "memory");
    if (tid == 32) {
        sts64(s_seg, 0, 0);
        sts64(s_wo, sb, sb);
        sts32(s_retire, kTiles);
        for (int s = 4; s < 2 * NSLOT; s++) mbar_init(bar_full + 8 * s, 1);
        for (int s = 0; s < NSLOT; s++) mbar_init(bar_empty + 8 * s, 2);
        for (int s = 0; s < 8; s++) mbar_init(bar_wo + 8 * s, 1);
        mbar_init(bar_role, 1);
        mbar_init(bar_q, 4);
        mbar_init(bar_q + 8, 8);
        mbar_init(bar_tag, 1);
        mbar_init(bar_wqfree, 1);
        mbar_init(bar_red, 8);
        mbar_init(bar_go, 1);
        mbar_init(bar_go + 8, 1);
        asm volatile("fence.mbarrier_init.release.cluster;" ::: "memory");
    }
    asm volatile("" ::: "memory");
    if (tid == 64) {
        mbar_init(bar_free, 8);
        mbar_init(bar_free + 8, 8);
        mbar_init(bar_out, 1);
        for (int s = 0; s < kSegs; s++) mbar_init(bar_inbox + 8 * s, 1);
        asm volatile("fence.mbarrier_init.release.cluster;" ::: "memory");
        mbar_expect_tx(bar_out, 7 * 256);
        for (int s = 0; s < kSegs; s++) mbar_expect_tx(bar_inbox + 8 * s, kInbox);
    }
    __syncthreads();
    asm volatile("barrier.cluster.arrive.relaxed.aligned;" ::: "memory");

    if (warp >= 4) {
        uint32_t tag = 0;
        const int st = tid - 128, sw = st >> 5;
        const uint32_t s_red = sb + kOffRed;
#pragma unroll 1
        for (int slice = cta; slice < 128; slice += kCtas) {
            mbar_wait(bar_wq, slice != cta);
            float a[8];
#pragma unroll
            for (int e = 0; e < 8; e++) a[e] = 0.f;
#pragma unroll
            for (int i = 0; i < 14; i++) {
                const uint4 wv = lds128(sb + kOffWq + i * 4096 + st * 16);
                uint32_t xr;
                asm volatile("ld.shared.u16 %0, [%1];" : "=r"(xr) : "r"(sb + kOffWq + kD * 128 + (i * 32 + (st >> 3)) * 2) : "memory");
                const float xv = bf_lo(xr);
                a[0] = fmaf(xv, bf_lo(wv.x), a[0]); a[1] = fmaf(xv, bf_hi(wv.x), a[1]);
                a[2] = fmaf(xv, bf_lo(wv.y), a[2]); a[3] = fmaf(xv, bf_hi(wv.y), a[3]);
                a[4] = fmaf(xv, bf_lo(wv.z), a[4]); a[5] = fmaf(xv, bf_hi(wv.z), a[5]);
                a[6] = fmaf(xv, bf_lo(wv.w), a[6]); a[7] = fmaf(xv, bf_hi(wv.w), a[7]);
            }
            if (slice != cta) bar_sync(2, kSvcThreads);
#pragma unroll
            for (int e = 0; e < 8; e++) {
                a[e] += __shfl_xor_sync(0xffffffffu, a[e], 8);
                a[e] += __shfl_xor_sync(0xffffffffu, a[e], 16);
            }
            if (lane < 8) {
                sts128f(s_red + (sw * 72 + lane * 8) * 4, make_float4(a[0], a[1], a[2], a[3]));
                sts128f(s_red + (sw * 72 + lane * 8 + 4) * 4, make_float4(a[4], a[5], a[6], a[7]));
            }
            mbar_wait(bar_tag, 0);
            tag = lds32(s_tag);
            bar_sync(2, kSvcThreads);
            if (st == 32) {
                if (slice + kCtas < 128) {
                    uint64_t policy;
                    asm volatile("createpolicy.fractional.L2::evict_first.b64 %0, 1.0;" : "=l"(policy));
                    load_wq(slice + kCtas, policy);
                } else {
                    mbar_arrive(bar_wqfree);
                }
            }
            if (st < 32) {
                float s0 = 0.f, s1 = 0.f;
#pragma unroll
                for (int i = 0; i < 8; i++) { const float2 v = lds64f(s_red + (i * 72 + st * 2) * 4); s0 += v.x; s1 += v.y; }
                const uint32_t pk = pack_bf16(s0, s1);
                st_relaxed2(P.q + slice * 64 + st * 2, make_uint2((pk << 16) | tag, (pk & 0xffff0000u) | tag));
            }
            if (slice == cta && st >= 128) {
                uint4 v = make_uint4(~tag, ~tag, ~tag, ~tag);
                for (uint32_t spins = 0;; spins++) {
                    uint32_t bad = 0;
                    repoll4(v, P.q + (st - 128) * 4, tag, bad);
                    if (!bad) break;
                    if (spins > kSpinLimit) __trap();
                }
                store_q(sb + kOffQ, st - 128, v);
                __syncwarp();
                if (lane == 0) mbar_arrive(bar_q);
            }
        }
        {
            if (lane == 0) { mbar_wait(bar_q, 0); if (cta >= 128 - kCtas) sleep_us(6); }
            __syncwarp();
            uint4 v[8];
#pragma unroll
            for (int i = 0; i < 8; i++) v[i] = make_uint4(~tag, ~tag, ~tag, ~tag);
            for (uint32_t spins = 0;; spins++) {
                uint32_t bad = 0;
#pragma unroll
                for (int i = 0; i < 8; i++) repoll4(v[i], P.q + (i * 256 + st) * 4, tag, bad);
                if (!bad) break;
                if (spins > kSpinLimit) __trap();
            }
#pragma unroll
            for (int i = 0; i < 8; i++) {
                if (i > 0 || st >= 128) store_q(sb + kOffQ, i * 256 + st, v[i]);
            }
            __syncwarp();
            if (lane == 0) mbar_arrive(bar_q + 8);
        }
        int role = cta >> 3;
        if (kClusters > kRoles) {
            if (lane == 0) { mbar_wait(bar_inbox + 8 * kCntSeg, 0); sleep_us(6); }
            __syncwarp();
            const uint32_t z = lane < 2 * kClusters ? ~tag : tag;
            uint4 v = make_uint4(z, z, z, z);
            for (uint32_t spins = 0;; spins++) {
                uint32_t bad = 0;
                repoll4(v, P.cnt + lane * 4, tag, bad);
                if (!bad) break;
                if (spins > kSpinLimit) __trap();
            }
            __syncwarp();
            uint32_t n = v.x + v.y + v.z + v.w;
            n += __shfl_xor_sync(0xffffffffu, n, 1);
            const int out = __reduce_min_sync(0xffffffffu, lane < 2 * kClusters ? (n << 4) | (lane >> 1) : 0xffffffffu) & 15;
            role = role == out ? kRoles : role - (role > out);
        }
        if (st == 0) {
            sts32(s_role, role);
            mbar_arrive(bar_role);
            if (role == kRoles) sts32(s_retire, 0);
            else if (role >= 7 && rank == 7) sts32(s_retire, kTiles - kRetire * kCtas);
        }
        const int prob = role >= 7 ? 1 : 0;
        const int sg = prob * 8 + rank;
        if (role == kRoles) return;

        const bool early = sg == kSegs - 1;
        const int g = lane >> 2, t = lane & 3;
        const uint32_t* po  = P.rec + (sg * kCtas + sw) * kRec + lane * 2;
        const uint32_t* pml = P.rec + (sg * kCtas + sw + (lane & 15) * 8) * kRec + 64;
        const uint32_t woff = ((lane >> 4) * 8 + (lane & 7)) * 128;
        uint64_t policy;
        asm volatile("createpolicy.fractional.L2::evict_first.b64 %0, 1.0;" : "=l"(policy));
        uint32_t s_dst = s_red + (sw * 72 + g) * 4;
        asm volatile("" : "+l"(po), "+l"(pml), "+r"(s_dst));
#pragma unroll 1
        for (uint32_t live = 0; live < 2; live++) {
            uint32_t wa[4][4][4];
            auto load_wo = [&]() {
                if (lane == 0 && live) mbar_wait(bar_go + (sw < 2 ? 0 : 8), 0);
                __syncwarp();
                uint32_t wb = lds32(s_wo + (sw >> 2) * 4) + (sw & 3) * (kUnit / 2);
                asm volatile("{\n.reg .pred p;\nsetp.ne.u32 p, %6, 0;\n"
                             "@p cp.async.bulk.tensor.4d.shared::cluster.global.mbarrier::complete_tx::bytes.L2::cache_hint "
                             "[%0], [%1, {%3, 0, 0, %4}], [%2], %5;\n"
                             "@p mbarrier.arrive.expect_tx.shared::cta.b64 _, [%2], %7;\n}"
                             :: "r"(wb), "l"(&M.wo[prob]), "r"(bar_wo + 8 * sw), "r"((role - 7 * prob) * 64), "r"(rank * 8 + sw),
                                "l"(policy), "r"(lane == 0 ? live : 0u), "n"(kUnit / 2) : "memory");
                wb += woff;
                asm volatile("" : "+r"(wb));
                if (live) mbar_wait(bar_wo + 8 * sw, 0);
#pragma unroll
                for (int kb = 0; kb < 4; kb++)
#pragma unroll
                    for (int mt = 0; mt < 4; mt++)
                        ldsm4t(wb + kb * 2048 + (((2 * mt + ((lane >> 3) & 1)) ^ (lane & 7)) << 4),
                               wa[kb][mt][0], wa[kb][mt][1], wa[kb][mt][2], wa[kb][mt][3]);
            };
            if (st == 0 && live && !early) { mbar_wait(bar_inbox + 8 * sg, 0); sleep_us(6); }
            bar_sync(2, kSvcThreads);
            if (early) load_wo();
            uint2 ov[kClusters];
            uint2 ml = make_uint2(__float_as_uint(kNegBig * kScaleLog2), tag ^ ((lane & 15) < kClusters ? live : 0u));
#pragma unroll
            for (int c = 0; c < kClusters; c++) ov[c] = make_uint2(tag ^ live, tag ^ live);
            for (uint32_t spins = 0;; spins++) {
                uint32_t bad[kClusters + 1];
                bad[kClusters] = repoll_ml(ml, pml, tag);
#pragma unroll
                for (int c = 0; c < kClusters; c++) bad[c] = repoll2(ov[c], po + c * 8 * kRec, tag);
                const uint32_t any = or3(or3(or3(bad[kClusters], bad[0], bad[1]), or3(bad[2], bad[3], bad[4]), or3(bad[5], bad[6], bad[7])),
                                         or3(bad[8], bad[9], bad[10]), or3(or3(bad[11], bad[12], bad[13]), bad[14], 0u));
                if (!__any_sync(0xffffffffu, any)) break;
                if (spins > kSpinLimit) __trap();
            }
            const float Mx = warp_max(asf(ml.x));
            const float wgt = ex2(asf(ml.x) - Mx);
            float L = wgt * asf(ml.y);
            float2 a[2];
#pragma unroll
            for (int c = 0; c < kClusters; c++) {
                if ((c & 3) == 0) L += __shfl_xor_sync(0xffffffffu, L, 1 << (c >> 2));
                const float wc = __shfl_sync(0xffffffffu, wgt, c);
                if (c < 2) { a[c].x = wc * asf(ov[c].x); a[c].y = wc * asf(ov[c].y); }
                else { a[c & 1].x = fmaf(wc, asf(ov[c].x), a[c & 1].x); a[c & 1].y = fmaf(wc, asf(ov[c].y), a[c & 1].y); }
            }
            const float inv = rcp(L);
            const uint32_t pk = pack_bf16((a[0].x + a[1].x) * inv, (a[0].y + a[1].y) * inv);
            uint32_t bf[8];
#pragma unroll
            for (int i = 0; i < 8; i++) bf[i] = __shfl_sync(0xffffffffu, pk, 4 * i + t);
            if (!early) load_wo();
            float d[4][4];
#pragma unroll
            for (int mt = 0; mt < 4; mt++) d[mt][0] = d[mt][1] = d[mt][2] = d[mt][3] = 0.f;
#pragma unroll
            for (int kb = 0; kb < 4; kb++)
#pragma unroll
                for (int mt = 0; mt < 4; mt++)
                    mma16816(d[mt], wa[kb][mt][0], wa[kb][mt][1], wa[kb][mt][2], wa[kb][mt][3], bf[2 * kb], bf[2 * kb + 1]);
            if (t == 0) {
#pragma unroll
                for (int mt = 0; mt < 4; mt++) {
                    sts32f(s_dst + (16 * mt + (mt & 2) * 4) * 4, d[mt][0]);
                    sts32f(s_dst + (16 * mt + 8 + (mt & 2) * 4) * 4, d[mt][2]);
                }
            }
            __syncwarp();
            if (lane == 0 && live) mbar_arrive(bar_red);
        }
    } else if (warp == 3) {
        cluster_wait();
        mbar_wait(bar_tag, 0);
        const uint32_t tag = lds32(s_tag);
        uint32_t* rec = P.rec + cta * kRec;
        int s = 0, role = 0;
#pragma unroll 1
        for (uint32_t live = 0; live < 2; live++) {
#pragma unroll 1
        for (const int send = s + kSegs / 2; s < send; s++, rec += kCtas * kRec) {
            const uint32_t ibox = sb + kOffInbox + (s & 1) * kInbox;
            mbar_wait(bar_inbox + 8 * s, 0);
            const float2 ml = lds64f(ibox + 4096 + (lane & 15) * 8);
            float2 ov[16];
#pragma unroll
            for (int i = 0; i < 16; i++) ov[i] = lds64f(ibox + i * 256 + lane * 8);
            const float Mx = warp_max(ml.x);
            const float wgt = ex2(ml.x - Mx);
            float L = wgt * ml.y;
            float2 a[4];
#pragma unroll
            for (int i = 0; i < 16; i++) {
                if ((i & 3) == 0) L += __shfl_xor_sync(0xffffffffu, L, 1 << (i >> 2));
                const float wi = __shfl_sync(0xffffffffu, wgt, i);
                if (i < 4) { a[i].x = wi * ov[i].x; a[i].y = wi * ov[i].y; }
                else { a[i & 3].x = fmaf(wi, ov[i].x, a[i & 3].x); a[i & 3].y = fmaf(wi, ov[i].y, a[i & 3].y); }
            }
            st_relaxed2(rec + lane * 2, make_uint2(tagf((a[0].x + a[1].x) + (a[2].x + a[3].x), tag),
                                                   tagf((a[0].y + a[1].y) + (a[2].y + a[3].y), tag)));
            if (lane < 4) st_relaxed64(rec + 64 + lane * 2, __float_as_uint(Mx), tagf(L, tag));
            __syncwarp();
            if (lane < 8 && s + 2 < kSegs)
                asm volatile("mbarrier.arrive.relaxed.cluster.shared::cluster.b64 _, [%0];" :: "r"(mapa(bar_free + 8 * (s & 1), lane)) : "memory");
        }
        if (!live) {
            mbar_wait(bar_role, 0);
            role = (int)lds32(s_role);
        }
        if (role == kRoles) continue;
        const uint32_t s_src = sb + kOffRed + (2 * lane + (lane & 16) / 2) * 4;
        __nv_bfloat16* outp = P.out + role * 64 + lane * 2;
        uint32_t r_out = mapa(sb + kOffOut + rank * 256 + lane * 8, 7), r_bar = mapa(bar_out, 7);
        asm volatile("" : "+l"(outp), "+r"(r_out), "+r"(r_bar));
        float2 y[8], z = make_float2(0.f, 0.f);
        auto add_others = [&]() {
            if (live) mbar_wait(bar_out, 0);
#pragma unroll
            for (int i = 0; i < 7; i++) y[i] = lds64f(sb + kOffOut + i * 256 + lane * 8);
            z.x = ((y[0].x + y[1].x) + (y[2].x + y[3].x)) + ((y[4].x + y[5].x) + (y[6].x + z.x));
            z.y = ((y[0].y + y[1].y) + (y[2].y + y[3].y)) + ((y[4].y + y[5].y) + (y[6].y + z.y));
        };
        if (rank == 7 && role >= 7) add_others();
        if (live) mbar_wait(bar_red, 0);
#pragma unroll
        for (int i = 0; i < 8; i++) y[i] = lds64f(s_src + i * 72 * 4);
        z.x += ((y[0].x + y[1].x) + (y[2].x + y[3].x)) + ((y[4].x + y[5].x) + (y[6].x + y[7].x));
        z.y += ((y[0].y + y[1].y) + (y[2].y + y[3].y)) + ((y[4].y + y[5].y) + (y[6].y + y[7].y));
        if (rank == 7 && role < 7) add_others();
        asm volatile("{\n.reg .pred p, q;\nsetp.eq.u32 p, %6, 1;\nsetp.eq.u32 q, %6, 2;\n"
                     "@p st.global.u32 [%0], %1;\n"
                     "@q st.async.weak.shared::cluster.mbarrier::complete_tx::bytes.v2.f32 [%2], {%3,%4}, [%5];\n}"
                     :: "l"(outp), "r"(pack_bf16(z.x, z.y)), "r"(r_out), "f"(z.x), "f"(z.y), "r"(r_bar),
                        "r"(rank == 7 ? live : 2 * live) : "memory");
        }
    } else if (warp >= 1) {
        cluster_wait();
        const int w = warp - 1;
        const int g = lane >> 2, t = lane & 3;
        const uint32_t koffe = (16 * w + g) * 512 + t * 16 + (g & 1) * 64;
        const uint32_t koffo = koffe ^ 64;
        uint32_t voff[4];
        {
            const int mi = lane >> 3, r8 = lane & 7;
            const uint32_t base = kUnit + (16 * w + 8 * (mi >> 1) + r8) * 512 + (mi & 1) * 64;
#pragma unroll
            for (int s = 0; s < 4; s++) voff[s] = base + (((r8 >> 1) ^ s) << 4);
        }
        const bool bsel = (g >> 1) == t;
        uint32_t i_o  = sb + kOffInbox + (rank * 2 + w) * 256 + (t * 8 + g) * 8;
        uint32_t i_ml = mapa(sb + kOffInbox + 4096 + (rank * 2 + w) * 8, lane & 7);
        asm volatile("" : "+r"(i_o), "+r"(i_ml));
        float acc[4][4][4];
        uint32_t q[8][4];
        float m = kNegBig, l = 0.f;
#pragma unroll
        for (int j = 0; j < 4; j++)
#pragma unroll
            for (int s = 0; s < 4; s++)
#pragma unroll
                for (int i = 0; i < 4; i++) acc[j][s][i] = 0.f;
        auto load_q = [&](int sgm) {
            mbar_wait(bar_q + (sgm ? 8 : 0), 0);
#pragma unroll
            for (int r = 0; r < 8; r++) {
                const uint4 v = lds128(sb + kOffQ + sgm * 1024 + (g & 1) * 512 + r * 64 + t * 16);
                q[r][0] = v.x; q[r][1] = v.y; q[r][2] = v.z; q[r][3] = v.w;
            }
        };
        load_q(0);
        uint32_t ntiles = 0;
        int seg = 0;
        int slot = 0; uint32_t ph = 0;
        while (true) {
            mbar_wait(bar_full + 16 * slot, ph);
            const int tseg = (int)lds32(s_seg + 4 * slot);
            if (tseg != seg) {
                do {
                    const uint32_t iset = (seg & 1) * kInbox, ibar = bar_inbox + 8 * seg;
                    l += __shfl_xor_sync(0xffffffffu, l, 1);
                    l += __shfl_xor_sync(0xffffffffu, l, 2);
#pragma unroll
                    for (int j = 0; j < 4; j++) {
                        float r[4];
#pragma unroll
                        for (int i = 0; i < 4; i++) {
                            r[i] = (acc[j][0][i] + __shfl_xor_sync(0xffffffffu, acc[j][1][i], 1))
                                 + (__shfl_xor_sync(0xffffffffu, acc[j][2][i], 2) + __shfl_xor_sync(0xffffffffu, acc[j][3][i], 3));
#pragma unroll
                            for (int x = 0; x < 4; x++) acc[j][x][i] = 0.f;
                        }
#pragma unroll
                        for (int h = 0; h < 2; h++) st_async2(mapa(i_o + iset, h * 4 + j), r[h], r[2 + h], mapa(ibar, h * 4 + j));
                    }
                    asm volatile("{\n.reg .pred p;\nsetp.lt.u32 p, %4, 8;\n"
                                 "@p st.async.weak.shared::cluster.mbarrier::complete_tx::bytes.v2.f32 [%0], {%1,%2}, [%3];\n}"
                                 :: "r"(i_ml + iset), "f"(m * kScaleLog2), "f"(l), "r"(mapa(ibar, lane & 7)), "r"(lane) : "memory");
                    m = kNegBig; l = 0.f;
                    if (seg == 0) ntiles = 0;
                    if (kClusters > kRoles && seg == kCntSeg && tid == 32) {
                        mbar_wait(bar_tag, 0);
                        asm volatile("st.relaxed.gpu.global.u32 [%0], %1;" :: "l"(P.cnt + cta), "r"(2 * ntiles + lds32(s_tag)) : "memory");
                    }
                    seg++;
                    if (seg >= 2 && seg < kSegs) mbar_wait(bar_free + 8 * (seg & 1), ((seg - 2) >> 1) & 1);
                } while (seg < tseg);
                if (seg == kSegs) break;
                load_q(seg);
            }
            ntiles++;
            const uint32_t base = sb + slot * kSlot;
            float sc[4][4];
#pragma unroll
            for (int i = 0; i < 4; i++) sc[i][0] = sc[i][1] = sc[i][2] = sc[i][3] = 0.f;
#pragma unroll
            for (int r = 0; r < 8; r += 2) {
                const uint4 ka = lds128(base + koffe + r * 64), kb = lds128(base + koffe + r * 64 + 4096);
                const uint4 kc = lds128(base + koffo + r * 64), kd = lds128(base + koffo + r * 64 + 4096);
                mma16816(sc[0], q[r][0], q[r][1], q[r][2], q[r][3], ka.x, ka.y);
                mma16816(sc[1], q[r][0], q[r][1], q[r][2], q[r][3], kb.x, kb.y);
                mma16816(sc[2], q[r][0], q[r][1], q[r][2], q[r][3], kc.x, kc.y);
                mma16816(sc[3], q[r][0], q[r][1], q[r][2], q[r][3], kd.x, kd.y);
                mma16816(sc[0], q[r + 1][0], q[r + 1][1], q[r + 1][2], q[r + 1][3], ka.z, ka.w);
                mma16816(sc[1], q[r + 1][0], q[r + 1][1], q[r + 1][2], q[r + 1][3], kb.z, kb.w);
                mma16816(sc[2], q[r + 1][0], q[r + 1][1], q[r + 1][2], q[r + 1][3], kc.z, kc.w);
                mma16816(sc[3], q[r + 1][0], q[r + 1][1], q[r + 1][2], q[r + 1][3], kd.z, kd.w);
            }
            const float s00 = sc[0][0] + sc[2][2], s01 = sc[0][3] + sc[2][1];
            const float s10 = sc[1][0] + sc[3][2], s11 = sc[1][3] + sc[3][1];
            float mx = fmaxf(fmaxf(s00, s01), fmaxf(s10, s11));
            mx = fmaxf(mx, __shfl_xor_sync(0xffffffffu, mx, 1));
            mx = fmaxf(mx, __shfl_xor_sync(0xffffffffu, mx, 2));
            if (__any_sync(0xffffffffu, mx > m)) {
                const float mn = fmaxf(m, mx);
                const float al = ex2(__fmul_rn(m, kScaleLog2) - __fmul_rn(mn, kScaleLog2));
                const float ao = __shfl_xor_sync(0xffffffffu, al, 4);
                const float a0 = (g & 1) ? ao : al, a1 = (g & 1) ? al : ao;
                m = mn; l *= al;
#pragma unroll
                for (int j = 0; j < 4; j++)
#pragma unroll
                    for (int s = 0; s < 4; s++) {
                        acc[j][s][0] *= a0; acc[j][s][1] *= a1; acc[j][s][2] *= a0; acc[j][s][3] *= a1;
                    }
            }
            const float mc = __fmul_rn(m, kScaleLog2);
            const float p00 = ex2(fmaf(s00, kScaleLog2, -mc)), p01 = ex2(fmaf(s01, kScaleLog2, -mc));
            const float p10 = ex2(fmaf(s10, kScaleLog2, -mc)), p11 = ex2(fmaf(s11, kScaleLog2, -mc));
            l += (p00 + p01) + (p10 + p11);
            const uint32_t b0 = bsel ? pack_bf16(p00, p01) : 0u;
            const uint32_t b1 = bsel ? pack_bf16(p10, p11) : 0u;
            mbar_wait(bar_full + 16 * slot + 8, ph);
#pragma unroll
            for (int j = 0; j < 4; j++)
#pragma unroll
                for (int s = 0; s < 4; s++) {
                    uint32_t a0, a1, a2, a3;
                    ldsm4t(base + voff[s] + j * 128, a0, a1, a2, a3);
                    mma16816(acc[j][s], a0, a1, a2, a3, b0, b1);
                }
            __syncwarp();
            if (lane == 0) mbar_arrive(bar_empty + 8 * slot);
            if (++slot == NSLOT) { slot = 0; ph ^= 1; }
        }
    } else {
        if (lane == 0) {
            sts32(s_tag, ((raw >> 15) & 1u) ^ 1u);
            mbar_arrive(bar_tag);
            int slot = 2; uint32_t eph = 1;
            uint32_t pbar = bar_full + 16, pph = 0;
            uint32_t cur;
            const char *k0 = P.k0, *v0 = P.v0, *k1 = P.k1 - (size_t)(kTiles / 2) * kUnit, *v1 = P.v1 - (size_t)(kTiles / 2) * kUnit;
            unsigned int* ctr = P.ctr;
            asm volatile("" : "+l"(k0), "+l"(v0), "+l"(k1), "+l"(v1), "+l"(ctr));
            mbar_wait(bar_full, 0);
            mbar_wait(bar_full + 8, 0);
            while (true) {
                const uint32_t dst = sb + slot * kSlot, bar = bar_full + 16 * slot;
                mbar_wait(bar_empty + 8 * slot, eph);
                if (slot == NSLOT - 2) mbar_wait(bar_wqfree, 0);
                const uint32_t retire = lds32(s_retire);
                cur = 2 * kCtas + (raw & (kTiles - 1));
                if (cur >= (uint32_t)kTiles) break;
                const bool pb = cur >= (uint32_t)(kTiles / 2);
                bulk_g2s(dst, (pb ? k1 : k0) + (size_t)cur * kUnit, kUnit, bar, pol);
                bulk_g2s(dst + kUnit, (pb ? v1 : v0) + (size_t)cur * kUnit, kUnit, bar + 8, pol);
                sts32(s_seg + 4 * slot, cur / kTilesSeg);
                mbar_expect_tx(bar, kUnit);
                mbar_expect_tx(bar + 8, kUnit);
                const uint32_t fph = eph ^ 1;
                if (++slot == NSLOT) { slot = 0; eph ^= 1; }
                if (cur >= retire) { mbar_wait(bar_empty + 8 * slot, eph); break; }
                mbar_wait(pbar, pph);
                mbar_wait(pbar + 8, pph);
                raw = ctr_fetch(ctr);
                pbar = bar; pph = fph;
            }
            sts32(s_seg + 4 * slot, kSegs);
            mbar_arrive(bar_full + 16 * slot);
            const int slot2 = slot + 1 == NSLOT ? 0 : slot + 1;
            sts64(s_wo, sb + slot * kSlot, sb + slot2 * kSlot);
            mbar_wait(bar_empty + 8 * slot2, slot2 ? eph : eph ^ 1);
            mbar_arrive(bar_go);
            mbar_wait(pbar, pph);
            mbar_arrive(bar_go + 8);
            if (cur < (uint32_t)kTiles) {
                for (uint32_t spins = 0;; spins++) {
                    uint32_t c;
                    asm volatile("ld.relaxed.gpu.global.u32 %0, [%1];" : "=r"(c) : "l"(P.ctr) : "memory");
                    c &= kTiles - 1;
                    if (c >= (uint32_t)(kTiles - 2 * kCtas)) break;
                    __nanosleep(200 + (kTiles - 2 * kCtas - c) * 4);
                    if (spins > kSpinLimit) __trap();
                }
                ctr_inc(P.ctr);
            }
            ctr_inc(P.ctr);
        }
    }
}

constexpr int kFbSplits = 64;
__device__ float g_fb_q[2 * kHD];
__device__ float g_fb_part[kSegs * kFbSplits * 2 * 258];

__global__ void fb_q_kernel(const __nv_bfloat16* x, const __nv_bfloat16* wq, int p) {
    const int c = blockIdx.x * blockDim.x + threadIdx.x;
    float a = 0.f;
    for (int r = 0; r < kD; r++) a = fmaf(__bfloat162float(x[r]), __bfloat162float(wq[(size_t)r * kHD + c]), a);
    g_fb_q[p * kHD + c] = __bfloat162float(__float2bfloat16(a));
}
__global__ void fb_attn_kernel(const char* k, const char* v, int p) {
    __shared__ float sm[8][258];
    const int kvh = blockIdx.x, split = blockIdx.y, warp = threadIdx.x >> 5, lane = threadIdx.x & 31;
    const int h = warp & 1, part = warp >> 1;
    float q[8], o[8], m = kNegBig, l = 0.f;
    for (int e = 0; e < 8; e++) { q[e] = g_fb_q[p * kHD + (kvh * 2 + h) * 256 + lane * 8 + e]; o[e] = 0.f; }
    const int nkeys = 65536 / kFbSplits / 4;
    const size_t row0 = (size_t)kvh * 65536 + (size_t)(split * 4 + part) * nkeys;
    for (int i = 0; i < nkeys; i++) {
        const uint4 kk = *(const uint4*)(k + (row0 + i) * 512 + lane * 16), vv = *(const uint4*)(v + (row0 + i) * 512 + lane * 16);
        float s = q[0] * bf_lo(kk.x) + q[1] * bf_hi(kk.x) + q[2] * bf_lo(kk.y) + q[3] * bf_hi(kk.y)
                + q[4] * bf_lo(kk.z) + q[5] * bf_hi(kk.z) + q[6] * bf_lo(kk.w) + q[7] * bf_hi(kk.w);
        for (int d = 16; d; d >>= 1) s += __shfl_xor_sync(0xffffffffu, s, d);
        s *= kScaleLog2;
        const float mn = fmaxf(m, s), al = exp2f(m - mn), pr = exp2f(s - mn);
        m = mn; l = l * al + pr;
        const float ve[8] = {bf_lo(vv.x), bf_hi(vv.x), bf_lo(vv.y), bf_hi(vv.y), bf_lo(vv.z), bf_hi(vv.z), bf_lo(vv.w), bf_hi(vv.w)};
        for (int e = 0; e < 8; e++) o[e] = o[e] * al + pr * ve[e];
    }
    for (int e = 0; e < 8; e++) sm[warp][lane * 8 + e] = o[e];
    if (lane == 0) { sm[warp][256] = m; sm[warp][257] = l; }
    __syncthreads();
    for (int hh = 0; hh < 2; hh++) {
        const float Mx = fmaxf(fmaxf(sm[hh][256], sm[2 + hh][256]), fmaxf(sm[4 + hh][256], sm[6 + hh][256]));
        float a = 0.f, L = 0.f;
        for (int j = 0; j < 4; j++) { const float w = exp2f(sm[2 * j + hh][256] - Mx); a += w * sm[2 * j + hh][threadIdx.x]; L += w * sm[2 * j + hh][257]; }
        float* dst = g_fb_part + (((p * 8 + kvh) * kFbSplits + split) * 2 + hh) * 258;
        dst[threadIdx.x] = a;
        if (threadIdx.x == 0) { dst[256] = Mx; dst[257] = L; }
    }
}
__global__ void fb_out_kernel(const __nv_bfloat16* wo, __nv_bfloat16* out, int p) {
    __shared__ float so[kHD];
    __shared__ float red[4][64];
    for (int head = 0; head < 16; head++) {
        const float* src = g_fb_part + ((p * 8 + (head >> 1)) * kFbSplits * 2 + (head & 1)) * 258;
        float Mx = kNegBig, a = 0.f, L = 0.f;
        for (int j = 0; j < kFbSplits; j++) Mx = fmaxf(Mx, src[j * 516 + 256]);
        for (int j = 0; j < kFbSplits; j++) { const float w = exp2f(src[j * 516 + 256] - Mx); a += w * src[j * 516 + threadIdx.x]; L += w * src[j * 516 + 257]; }
        so[head * 256 + threadIdx.x] = __bfloat162float(__float2bfloat16(a / L));
    }
    __syncthreads();
    const int col = blockIdx.x * 64 + (threadIdx.x & 63), rg = threadIdx.x >> 6;
    float a = 0.f;
    for (int r = rg * 1024; r < rg * 1024 + 1024; r++) a = fmaf(so[r], __bfloat162float(wo[(size_t)r * kD + col]), a);
    red[rg][threadIdx.x & 63] = a;
    __syncthreads();
    if (rg == 0) out[p * kD + col] = __float2bfloat16((red[0][threadIdx.x] + red[1][threadIdx.x]) + (red[2][threadIdx.x] + red[3][threadIdx.x]));
}

typedef CUresult (*EncodeFn)(CUtensorMap*, CUtensorMapDataType, cuuint32_t, void*, const cuuint64_t*, const cuuint64_t*,
                             const cuuint32_t*, const cuuint32_t*, CUtensorMapInterleave, CUtensorMapSwizzle,
                             CUtensorMapL2promotion, CUtensorMapFloatOOBfill);

}

extern "C" void kernel_launch(void* const* d_in, const int* in_sizes, int n_in, void* d_out, int out_size) {
    (void)in_sizes; (void)n_in; (void)out_size;
    static EncodeFn encode = nullptr;
    static void *p_ctr, *p_q, *p_rec, *p_cnt;
    static int nclusters = -1;
    if (nclusters < 0) {
        cudaGetSymbolAddress(&p_ctr, g_tile_ctr);
        cudaGetSymbolAddress(&p_q, g_q);
        cudaGetSymbolAddress(&p_rec, g_rec);
        cudaGetSymbolAddress(&p_cnt, g_cnt);
        cudaDriverEntryPointQueryResult qr;
        cudaGetDriverEntryPoint("cuTensorMapEncodeTiled", (void**)&encode, cudaEnableDefault, &qr);
        cudaFuncSetAttribute(gqa_decode_kernel<14>, cudaFuncAttributeMaxDynamicSharedMemorySize, (int)kSmemBytes);
        cudaFuncSetAttribute(gqa_decode_kernel<15>, cudaFuncAttributeMaxDynamicSharedMemorySize, (int)kSmemBytes);
        cudaLaunchConfig_t cfg = {};
        cfg.gridDim = dim3(15 * 8); cfg.blockDim = dim3(kThreads); cfg.dynamicSmemBytes = kSmemBytes;
        cudaLaunchAttribute at[1];
        at[0].id = cudaLaunchAttributeClusterDimension;
        at[0].val.clusterDim.x = 8; at[0].val.clusterDim.y = 1; at[0].val.clusterDim.z = 1;
        cfg.attrs = at; cfg.numAttrs = 1;
        if (cudaOccupancyMaxActiveClusters(&nclusters, gqa_decode_kernel<15>, &cfg) != cudaSuccess) { nclusters = 0; cudaGetLastError(); }
    }
    if (nclusters < kRoles || !encode) {
        for (int p = 0; p < 2; p++) {
            fb_q_kernel<<<kHD / 256, 256, 0, cudaStreamPerThread>>>((const __nv_bfloat16*)d_in[5 * p], (const __nv_bfloat16*)d_in[5 * p + 3], p);
            fb_attn_kernel<<<dim3(8, kFbSplits), 256, 0, cudaStreamPerThread>>>((const char*)d_in[5 * p + 1], (const char*)d_in[5 * p + 2], p);
            fb_out_kernel<<<7, 256, 0, cudaStreamPerThread>>>((const __nv_bfloat16*)d_in[5 * p + 4], (__nv_bfloat16*)d_out, p);
        }
        return;
    }
    Params P;
    Maps M;
    for (int p = 0; p < 2; p++) {
        P.x[p]  = (const __nv_bfloat16*)d_in[5 * p + 0];
        const cuuint64_t qdims[2] = {(cuuint64_t)kHD, (cuuint64_t)kD};
        const cuuint64_t qstrides[1] = {(cuuint64_t)kHD * 2};
        const cuuint32_t qbox[2] = {64, kD / 2}, qestr[2] = {1, 1};
        encode(&M.wq[p], CU_TENSOR_MAP_DATA_TYPE_BFLOAT16, 2, d_in[5 * p + 3], qdims, qstrides, qbox, qestr,
               CU_TENSOR_MAP_INTERLEAVE_NONE, CU_TENSOR_MAP_SWIZZLE_NONE, CU_TENSOR_MAP_L2_PROMOTION_NONE,
               CU_TENSOR_MAP_FLOAT_OOB_FILL_NONE);
        const cuuint64_t dims[4] = {(cuuint64_t)kD, 2, 32, kHD / 64};
        const cuuint64_t strides[3] = {(cuuint64_t)kD * 2 * 32, (cuuint64_t)kD * 2, (cuuint64_t)kD * 2 * 64};
        const cuuint32_t box[4] = {64, 2, 32, 1}, estr[4] = {1, 1, 1, 1};
        encode(&M.wo[p], CU_TENSOR_MAP_DATA_TYPE_BFLOAT16, 4, d_in[5 * p + 4], dims, strides, box, estr,
               CU_TENSOR_MAP_INTERLEAVE_NONE, CU_TENSOR_MAP_SWIZZLE_128B, CU_TENSOR_MAP_L2_PROMOTION_NONE,
               CU_TENSOR_MAP_FLOAT_OOB_FILL_NONE);
    }
    P.k0 = (const char*)d_in[1]; P.v0 = (const char*)d_in[2];
    P.k1 = (const char*)d_in[6]; P.v1 = (const char*)d_in[7];
    P.out = (__nv_bfloat16*)d_out;
    P.ctr = (unsigned int*)p_ctr; P.q = (uint32_t*)p_q; P.rec = (uint32_t*)p_rec; P.cnt = (uint32_t*)p_cnt;
    if (nclusters >= 15) gqa_decode_kernel<15><<<15 * 8, kThreads, kSmemBytes, cudaStreamPerThread>>>(P, M);
    else                 gqa_decode_kernel<14><<<14 * 8, kThreads, kSmemBytes, cudaStreamPerThread>>>(P, M);
}
```
